```python
import torch

def _softmax(x, axis=-1):
    return torch.softmax(x, dim=axis)
def _gelu(x):
    return torch.nn.functional.gelu(x, approximate="tanh")
def _silu(x):
    return torch.nn.functional.silu(x)
def _sigmoid(x):
    return torch.sigmoid(x)
def _layernorm(x, axis=-1, eps=1e-5):
    m = x.mean(dim=axis, keepdim=True)
    v = x.var(dim=axis, keepdim=True, unbiased=False)
    return (x - m) / torch.sqrt(v + eps)
def _scatter_add(tgt, idx, src, axis=0):
    return tgt.clone().index_add_(axis, idx, src)
def _segment_sum(src, seg, n):
    out = torch.zeros((n,) + src.shape[1:], dtype=src.dtype)
    return out.index_add_(0, seg, src)
def _pad(x, pw):
    flat = tuple(v for pair in reversed(pw) for v in pair)
    return torch.nn.functional.pad(x, flat)

kernel_name = 'sequential_preLN__mha_block__geglu_ffn__prompt'

def setup_inputs():

    _w = (lambda a: (lambda t: t.to(torch.bfloat16) if t.is_floating_point() else t)(torch.as_tensor(a)))
    def _A_setup():
        B, S, D, H = 1, 2048, 640, 32
        return {
            "x": _w((lambda *s: torch.randn(*s, dtype=torch.bfloat16) * 0.05)(B, S, D)),
            "wqkv": _w((lambda *s: torch.randn(*s, dtype=torch.bfloat16) * 0.05)(D, 3 * D)),
            "wo": _w((lambda *s: torch.randn(*s, dtype=torch.bfloat16) * 0.05)(D, D)),
        }
    _A_in = _A_setup()

    def _B_setup():
        B, S, D, F = 1, 2048, 640, 1536
        return {
            "x": _w((lambda *s: torch.randn(*s, dtype=torch.bfloat16) * 0.05)(B, S, D)),
            "w_gate": _w((lambda *s: torch.randn(*s, dtype=torch.bfloat16) * 0.05)(D, F)),
            "w_up": _w((lambda *s: torch.randn(*s, dtype=torch.bfloat16) * 0.05)(D, F)),
            "w_down": _w((lambda *s: torch.randn(*s, dtype=torch.bfloat16) * 0.05)(F, D)),
        }
    _B_in = _B_setup()

    return {
        "A_x": _A_in["x"],
        "A_wqkv": _A_in["wqkv"],
        "A_wo": _A_in["wo"],
        "B_x": _B_in["x"],
        "B_w_gate": _B_in["w_gate"],
        "B_w_up": _B_in["w_up"],
        "B_w_down": _B_in["w_down"],
    }

def reference(A_x, A_wqkv, A_wo, B_x, B_w_gate, B_w_up, B_w_down):
    def _A_ref(x, wqkv, wo):
        B, S, D = x.shape
        H = 32
        Dh = D // H
        qkv = (lambda x, *d: x.permute(*d))((x @ wqkv).reshape(B, S, 3, H, Dh), 2, 0, 3, 1, 4)
        q, k, v = qkv[0], qkv[1], qkv[2]
        scores = torch.einsum("bhqd,bhkd->bhqk", q, k) * (Dh ** -0.5)
        p = _softmax(scores, axis=-1)
        o = torch.einsum("bhqk,bhkd->bhqd", p, v)
        return (lambda x, *d: x.permute(*d))(o, 0, 2, 1, 3).reshape(B, S, D) @ wo

    def _B_ref(x, w_gate, w_up, w_down):
        return (_gelu(x @ w_gate) * (x @ w_up)) @ w_down

    x = A_x
    h = x + _A_ref(_layernorm(x, axis=-1), A_wqkv, A_wo)
    h2 = h + _B_ref(_layernorm(h, axis=-1), B_w_gate, B_w_up, B_w_down)
    return h2
```

```cpp
#include <cuda_runtime.h>
#include <cuda_bf16.h>
#include <cuda.h>
#include <stdint.h>

namespace {

constexpr int S_ = 2048, D_ = 640, F_ = 1536;
constexpr int PLANE = S_ * 16;
constexpr float LN_EPS = 1e-5f;
constexpr uint32_t POLY_MASK = 0xD5D5u;

__device__ __align__(1024) uint8_t g_qkv[96 * 3 * PLANE];
__device__ __align__(1024) uint8_t g_o[16 * 80 * 2048];
__device__ __align__(1024) uint8_t g_h[16 * 80 * 2048];
__device__ __align__(1024) uint8_t g_H[16 * 192 * 2048];
__device__ __align__(1024) uint8_t g_wo[8 * 80 * 1280];
__device__ __align__(1024) uint8_t g_wd[8 * 192 * 1280];
__device__ __align__(16) float2 g_st1[S_];
__device__ __align__(16) float g_cs1[16 * 1920];
__device__ __align__(16) float g_cs2[16 * 3072];
__device__ __align__(16) float2 g_st2[S_ * 8];
__device__ unsigned g_flags[64 * 32];
constexpr int FL_ROW = 0, FL_COL = 16, FL_C = 24, FL_D = 40, FL_N = 56;

#define WG_FENCE() asm volatile("wgmma.fence.sync.aligned;" ::: "memory")
#define WG_COMMIT() asm volatile("wgmma.commit_group.sync.aligned;" ::: "memory")
#define WG_WAIT(n) asm volatile("wgmma.wait_group.sync.aligned %0;" ::"n"(n) : "memory")
__device__ __forceinline__ uint64_t mkdesc(uint32_t addr, uint32_t lbo, uint32_t sbo, int swz) {
  return (uint64_t)((addr & 0x3FFFF) >> 4) | ((uint64_t)(lbo >> 4) << 16) | ((uint64_t)(sbo >> 4) << 32) | ((uint64_t)swz << 62);
}
__device__ __forceinline__ uint32_t smem_u32(const void* p) { return (uint32_t)__cvta_generic_to_shared(p); }
__device__ __forceinline__ void mbar_init(uint32_t bar, int cnt) { asm volatile("mbarrier.init.shared::cta.b64 [%0], %1;" ::"r"(bar), "r"(cnt) : "memory"); }
__device__ __forceinline__ void mbar_expect(uint32_t bar, uint32_t bytes) { asm volatile("mbarrier.arrive.expect_tx.shared::cta.b64 _, [%0], %1;" ::"r"(bar), "r"(bytes) : "memory"); }
__device__ __forceinline__ void mbar_arrive(uint32_t bar) { asm volatile("mbarrier.arrive.shared::cta.b64 _, [%0];" ::"r"(bar) : "memory"); }
__device__ __forceinline__ void mbar_wait(uint32_t bar, uint32_t par) {
  asm volatile("{\n.reg .pred p;\n.reg .u32 c;\nmov.u32 c, 0;\nLW:\nmbarrier.try_wait.parity.shared::cta.b64 p, [%0], %1;\n@p bra LD;\n"
               "add.u32 c, c, 1;\nsetp.lt.u32 p, c, 2000000;\n@p bra LW;\ntrap;\nLD:\n}" ::"r"(bar), "r"(par) : "memory");
}
__device__ __forceinline__ void bulk_g2s(uint32_t dst, const void* src, uint32_t bytes, uint32_t bar) {
  asm volatile("cp.async.bulk.shared::cluster.global.mbarrier::complete_tx::bytes [%0], [%1], %2, [%3];" ::"r"(dst), "l"(src), "r"(bytes), "r"(bar) : "memory");
}
__device__ __forceinline__ void tma2d(uint32_t dst, const CUtensorMap* tm, int c0, int c1, uint32_t bar) {
  asm volatile("cp.async.bulk.tensor.2d.shared::cluster.global.mbarrier::complete_tx::bytes [%0], [%1, {%3, %4}], [%2];" ::"r"(dst), "l"(tm), "r"(bar), "r"(c0), "r"(c1) : "memory");
}
__device__ __forceinline__ void tma3d(uint32_t dst, const CUtensorMap* tm, int c0, int c1, int c2, uint32_t bar) {
  asm volatile("cp.async.bulk.tensor.3d.shared::cluster.global.mbarrier::complete_tx::bytes [%0], [%1, {%3, %4, %5}], [%2];" ::"r"(dst), "l"(tm), "r"(bar), "r"(c0), "r"(c1), "r"(c2) : "memory");
}
__device__ __forceinline__ bool elect_one() {
  uint32_t p;
  asm volatile("{\n.reg .pred e;\nelect.sync _|e, 0xffffffff;\nselp.u32 %0, 1, 0, e;\n}" : "=r"(p));
  return p;
}
__device__ __forceinline__ void bar_sync(int id, int n) { asm volatile("bar.sync %0, %1;" ::"r"(id), "r"(n) : "memory"); }
__device__ __forceinline__ void flag_add(unsigned* f) { asm volatile("fence.acq_rel.gpu;\nred.relaxed.gpu.global.add.u32 [%0], 1;" ::"l"(f) : "memory"); }
__device__ __forceinline__ void flag_wait(const unsigned* f, unsigned n) {
  for (int i = 0; i < 4000000; i++) {
    unsigned v;
    asm volatile("ld.acquire.gpu.global.u32 %0, [%1];" : "=r"(v) : "l"(f) : "memory");
    if (v >= n) return;
  }
  __trap();
}
__device__ __forceinline__ float ex2f(float x) { float y; asm("ex2.approx.ftz.f32 %0, %1;" : "=f"(y) : "f"(x)); return y; }
__device__ __forceinline__ float tanhf_(float x) { float y; asm("tanh.approx.f32 %0, %1;" : "=f"(y) : "f"(x)); return y; }
__device__ __forceinline__ uint32_t packbf(float lo, float hi) { uint32_t r; asm("cvt.rn.bf16x2.f32 %0, %1, %2;" : "=r"(r) : "f"(hi), "f"(lo)); return r; }
__device__ __forceinline__ float bflo(uint32_t v) { return __uint_as_float(v << 16); }
__device__ __forceinline__ float bfhi(uint32_t v) { return __uint_as_float(v & 0xFFFF0000u); }
template <int N> __device__ __forceinline__ void fence_f(float (&a)[N]) {
#pragma unroll
  for (int i = 0; i < N; i++) asm volatile("" : "+f"(a[i])::"memory");
}
template <int N> __device__ __forceinline__ void fence_u(uint32_t (&a)[N]) {
#pragma unroll
  for (int i = 0; i < N; i++) asm volatile("" : "+r"(a[i])::"memory");
}

template<int TB> __device__ __forceinline__ void wgmma_n240_ss(float (&d)[120], uint64_t da, uint64_t db, int scale_d) {
  asm volatile("{\n.reg .pred p;\nsetp.ne.b32 p, %122, 0;\n"
    "wgmma.mma_async.sync.aligned.m64n240k16.f32.bf16.bf16 "
    "{%0, %1, %2, %3, %4, %5, %6, %7, %8, %9, %10, %11, %12, %13, %14, %15, %16, %17, %18, %19, %20, %21, %22, %23, "
    "%24, %25, %26, %27, %28, %29, %30, %31, %32, %33, %34, %35, %36, %37, %38, %39, %40, %41, %42, %43, %44, %45, %46, %47, "
    "%48, %49, %50, %51, %52, %53, %54, %55, %56, %57, %58, %59, %60, %61, %62, %63, %64, %65, %66, %67, %68, %69, %70, %71, "
    "%72, %73, %74, %75, %76, %77, %78, %79, %80, %81, %82, %83, %84, %85, %86, %87, %88, %89, %90, %91, %92, %93, %94, %95, "
    "%96, %97, %98, %99, %100, %101, %102, %103, %104, %105, %106, %107, %108, %109, %110, %111, %112, %113, %114, %115, %116, %117, %118, %119}, "
    "%120, %121, p, 1, 1, 0, %123;\n}\n"
    : "+f"(d[0]), "+f"(d[1]), "+f"(d[2]), "+f"(d[3]), "+f"(d[4]), "+f"(d[5]), "+f"(d[6]), "+f"(d[7]), "+f"(d[8]), "+f"(d[9]), "+f"(d[10]), "+f"(d[11]),
      "+f"(d[12]), "+f"(d[13]), "+f"(d[14]), "+f"(d[15]), "+f"(d[16]), "+f"(d[17]), "+f"(d[18]), "+f"(d[19]), "+f"(d[20]), "+f"(d[21]), "+f"(d[22]), "+f"(d[23]),
      "+f"(d[24]), "+f"(d[25]), "+f"(d[26]), "+f"(d[27]), "+f"(d[28]), "+f"(d[29]), "+f"(d[30]), "+f"(d[31]), "+f"(d[32]), "+f"(d[33]), "+f"(d[34]), "+f"(d[35]),
      "+f"(d[36]), "+f"(d[37]), "+f"(d[38]), "+f"(d[39]), "+f"(d[40]), "+f"(d[41]), "+f"(d[42]), "+f"(d[43]), "+f"(d[44]), "+f"(d[45]), "+f"(d[46]), "+f"(d[47]),
      "+f"(d[48]), "+f"(d[49]), "+f"(d[50]), "+f"(d[51]), "+f"(d[52]), "+f"(d[53]), "+f"(d[54]), "+f"(d[55]), "+f"(d[56]), "+f"(d[57]), "+f"(d[58]), "+f"(d[59]),
      "+f"(d[60]), "+f"(d[61]), "+f"(d[62]), "+f"(d[63]), "+f"(d[64]), "+f"(d[65]), "+f"(d[66]), "+f"(d[67]), "+f"(d[68]), "+f"(d[69]), "+f"(d[70]), "+f"(d[71]),
      "+f"(d[72]), "+f"(d[73]), "+f"(d[74]), "+f"(d[75]), "+f"(d[76]), "+f"(d[77]), "+f"(d[78]), "+f"(d[79]), "+f"(d[80]), "+f"(d[81]), "+f"(d[82]), "+f"(d[83]),
      "+f"(d[84]), "+f"(d[85]), "+f"(d[86]), "+f"(d[87]), "+f"(d[88]), "+f"(d[89]), "+f"(d[90]), "+f"(d[91]), "+f"(d[92]), "+f"(d[93]), "+f"(d[94]), "+f"(d[95]),
      "+f"(d[96]), "+f"(d[97]), "+f"(d[98]), "+f"(d[99]), "+f"(d[100]), "+f"(d[101]), "+f"(d[102]), "+f"(d[103]), "+f"(d[104]), "+f"(d[105]), "+f"(d[106]), "+f"(d[107]),
      "+f"(d[108]), "+f"(d[109]), "+f"(d[110]), "+f"(d[111]), "+f"(d[112]), "+f"(d[113]), "+f"(d[114]), "+f"(d[115]), "+f"(d[116]), "+f"(d[117]), "+f"(d[118]), "+f"(d[119])
    : "l"(da), "l"(db), "r"(scale_d), "n"(TB));
}
template<int TB> __device__ __forceinline__ void wgmma_n192_ss(float (&d)[96], uint64_t da, uint64_t db, int scale_d) {
  asm volatile("{\n.reg .pred p;\nsetp.ne.b32 p, %98, 0;\n"
    "wgmma.mma_async.sync.aligned.m64n192k16.f32.bf16.bf16 "
    "{%0, %1, %2, %3, %4, %5, %6, %7, %8, %9, %10, %11, %12, %13, %14, %15, %16, %17, %18, %19, %20, %21, %22, %23, "
    "%24, %25, %26, %27, %28, %29, %30, %31, %32, %33, %34, %35, %36, %37, %38, %39, %40, %41, %42, %43, %44, %45, %46, %47, "
    "%48, %49, %50, %51, %52, %53, %54, %55, %56, %57, %58, %59, %60, %61, %62, %63, %64, %65, %66, %67, %68, %69, %70, %71, "
    "%72, %73, %74, %75, %76, %77, %78, %79, %80, %81, %82, %83, %84, %85, %86, %87, %88, %89, %90, %91, %92, %93, %94, %95}, "
    "%96, %97, p, 1, 1, 0, %99;\n}\n"
    : "+f"(d[0]), "+f"(d[1]), "+f"(d[2]), "+f"(d[3]), "+f"(d[4]), "+f"(d[5]), "+f"(d[6]), "+f"(d[7]), "+f"(d[8]), "+f"(d[9]), "+f"(d[10]), "+f"(d[11]),
      "+f"(d[12]), "+f"(d[13]), "+f"(d[14]), "+f"(d[15]), "+f"(d[16]), "+f"(d[17]), "+f"(d[18]), "+f"(d[19]), "+f"(d[20]), "+f"(d[21]), "+f"(d[22]), "+f"(d[23]),
      "+f"(d[24]), "+f"(d[25]), "+f"(d[26]), "+f"(d[27]), "+f"(d[28]), "+f"(d[29]), "+f"(d[30]), "+f"(d[31]), "+f"(d[32]), "+f"(d[33]), "+f"(d[34]), "+f"(d[35]),
      "+f"(d[36]), "+f"(d[37]), "+f"(d[38]), "+f"(d[39]), "+f"(d[40]), "+f"(d[41]), "+f"(d[42]), "+f"(d[43]), "+f"(d[44]), "+f"(d[45]), "+f"(d[46]), "+f"(d[47]),
      "+f"(d[48]), "+f"(d[49]), "+f"(d[50]), "+f"(d[51]), "+f"(d[52]), "+f"(d[53]), "+f"(d[54]), "+f"(d[55]), "+f"(d[56]), "+f"(d[57]), "+f"(d[58]), "+f"(d[59]),
      "+f"(d[60]), "+f"(d[61]), "+f"(d[62]), "+f"(d[63]), "+f"(d[64]), "+f"(d[65]), "+f"(d[66]), "+f"(d[67]), "+f"(d[68]), "+f"(d[69]), "+f"(d[70]), "+f"(d[71]),
      "+f"(d[72]), "+f"(d[73]), "+f"(d[74]), "+f"(d[75]), "+f"(d[76]), "+f"(d[77]), "+f"(d[78]), "+f"(d[79]), "+f"(d[80]), "+f"(d[81]), "+f"(d[82]), "+f"(d[83]),
      "+f"(d[84]), "+f"(d[85]), "+f"(d[86]), "+f"(d[87]), "+f"(d[88]), "+f"(d[89]), "+f"(d[90]), "+f"(d[91]), "+f"(d[92]), "+f"(d[93]), "+f"(d[94]), "+f"(d[95])
    : "l"(da), "l"(db), "r"(scale_d), "n"(TB));
}
template<int TB> __device__ __forceinline__ void wgmma_n80_ss(float (&d)[40], uint64_t da, uint64_t db, int scale_d) {
  asm volatile("{\n.reg .pred p;\nsetp.ne.b32 p, %42, 0;\n"
    "wgmma.mma_async.sync.aligned.m64n80k16.f32.bf16.bf16 "
    "{%0, %1, %2, %3, %4, %5, %6, %7, %8, %9, %10, %11, %12, %13, %14, %15, %16, %17, %18, %19, %20, %21, %22, %23, "
    "%24, %25, %26, %27, %28, %29, %30, %31, %32, %33, %34, %35, %36, %37, %38, %39}, "
    "%40, %41, p, 1, 1, 0, %43;\n}\n"
    : "+f"(d[0]), "+f"(d[1]), "+f"(d[2]), "+f"(d[3]), "+f"(d[4]), "+f"(d[5]), "+f"(d[6]), "+f"(d[7]), "+f"(d[8]), "+f"(d[9]), "+f"(d[10]), "+f"(d[11]),
      "+f"(d[12]), "+f"(d[13]), "+f"(d[14]), "+f"(d[15]), "+f"(d[16]), "+f"(d[17]), "+f"(d[18]), "+f"(d[19]), "+f"(d[20]), "+f"(d[21]), "+f"(d[22]), "+f"(d[23]),
      "+f"(d[24]), "+f"(d[25]), "+f"(d[26]), "+f"(d[27]), "+f"(d[28]), "+f"(d[29]), "+f"(d[30]), "+f"(d[31]), "+f"(d[32]), "+f"(d[33]), "+f"(d[34]), "+f"(d[35]),
      "+f"(d[36]), "+f"(d[37]), "+f"(d[38]), "+f"(d[39])
    : "l"(da), "l"(db), "r"(scale_d), "n"(TB));
}
template<int TB> __device__ __forceinline__ void wgmma_n128_rs(float (&d)[64], uint32_t a0, uint32_t a1, uint32_t a2, uint32_t a3, uint64_t db) {
  asm volatile("{\n.reg .pred p;\nsetp.ne.b32 p, 1, 0;\n"
    "wgmma.mma_async.sync.aligned.m64n128k16.f32.bf16.bf16 "
    "{%0, %1, %2, %3, %4, %5, %6, %7, %8, %9, %10, %11, %12, %13, %14, %15, %16, %17, %18, %19, %20, %21, %22, %23, "
    "%24, %25, %26, %27, %28, %29, %30, %31, %32, %33, %34, %35, %36, %37, %38, %39, %40, %41, %42, %43, %44, %45, %46, %47, "
    "%48, %49, %50, %51, %52, %53, %54, %55, %56, %57, %58, %59, %60, %61, %62, %63}, "
    "{%64, %65, %66, %67}, %68, p, 1, 1, %69;\n}\n"
    : "+f"(d[0]), "+f"(d[1]), "+f"(d[2]), "+f"(d[3]), "+f"(d[4]), "+f"(d[5]), "+f"(d[6]), "+f"(d[7]), "+f"(d[8]), "+f"(d[9]), "+f"(d[10]), "+f"(d[11]),
      "+f"(d[12]), "+f"(d[13]), "+f"(d[14]), "+f"(d[15]), "+f"(d[16]), "+f"(d[17]), "+f"(d[18]), "+f"(d[19]), "+f"(d[20]), "+f"(d[21]), "+f"(d[22]), "+f"(d[23]),
      "+f"(d[24]), "+f"(d[25]), "+f"(d[26]), "+f"(d[27]), "+f"(d[28]), "+f"(d[29]), "+f"(d[30]), "+f"(d[31]), "+f"(d[32]), "+f"(d[33]), "+f"(d[34]), "+f"(d[35]),
      "+f"(d[36]), "+f"(d[37]), "+f"(d[38]), "+f"(d[39]), "+f"(d[40]), "+f"(d[41]), "+f"(d[42]), "+f"(d[43]), "+f"(d[44]), "+f"(d[45]), "+f"(d[46]), "+f"(d[47]),
      "+f"(d[48]), "+f"(d[49]), "+f"(d[50]), "+f"(d[51]), "+f"(d[52]), "+f"(d[53]), "+f"(d[54]), "+f"(d[55]), "+f"(d[56]), "+f"(d[57]), "+f"(d[58]), "+f"(d[59]),
      "+f"(d[60]), "+f"(d[61]), "+f"(d[62]), "+f"(d[63])
    : "r"(a0), "r"(a1), "r"(a2), "r"(a3), "l"(db), "n"(TB));
}
template<int TB> __device__ __forceinline__ void wgmma_n128_rs_z(float (&d)[64], uint32_t a0, uint32_t a1, uint32_t a2, uint32_t a3, uint64_t db) {
  asm volatile("{\n.reg .pred p;\nsetp.ne.b32 p, 0, 0;\n"
    "wgmma.mma_async.sync.aligned.m64n128k16.f32.bf16.bf16 "
    "{%0, %1, %2, %3, %4, %5, %6, %7, %8, %9, %10, %11, %12, %13, %14, %15, %16, %17, %18, %19, %20, %21, %22, %23, "
    "%24, %25, %26, %27, %28, %29, %30, %31, %32, %33, %34, %35, %36, %37, %38, %39, %40, %41, %42, %43, %44, %45, %46, %47, "
    "%48, %49, %50, %51, %52, %53, %54, %55, %56, %57, %58, %59, %60, %61, %62, %63}, "
    "{%64, %65, %66, %67}, %68, p, 1, 1, %69;\n}\n"
    : "=f"(d[0]), "=f"(d[1]), "=f"(d[2]), "=f"(d[3]), "=f"(d[4]), "=f"(d[5]), "=f"(d[6]), "=f"(d[7]), "=f"(d[8]), "=f"(d[9]), "=f"(d[10]), "=f"(d[11]),
      "=f"(d[12]), "=f"(d[13]), "=f"(d[14]), "=f"(d[15]), "=f"(d[16]), "=f"(d[17]), "=f"(d[18]), "=f"(d[19]), "=f"(d[20]), "=f"(d[21]), "=f"(d[22]), "=f"(d[23]),
      "=f"(d[24]), "=f"(d[25]), "=f"(d[26]), "=f"(d[27]), "=f"(d[28]), "=f"(d[29]), "=f"(d[30]), "=f"(d[31]), "=f"(d[32]), "=f"(d[33]), "=f"(d[34]), "=f"(d[35]),
      "=f"(d[36]), "=f"(d[37]), "=f"(d[38]), "=f"(d[39]), "=f"(d[40]), "=f"(d[41]), "=f"(d[42]), "=f"(d[43]), "=f"(d[44]), "=f"(d[45]), "=f"(d[46]), "=f"(d[47]),
      "=f"(d[48]), "=f"(d[49]), "=f"(d[50]), "=f"(d[51]), "=f"(d[52]), "=f"(d[53]), "=f"(d[54]), "=f"(d[55]), "=f"(d[56]), "=f"(d[57]), "=f"(d[58]), "=f"(d[59]),
      "=f"(d[60]), "=f"(d[61]), "=f"(d[62]), "=f"(d[63])
    : "r"(a0), "r"(a1), "r"(a2), "r"(a3), "l"(db), "n"(TB));
}
template<int TB> __device__ __forceinline__ void wgmma_n64_rs(float (&d)[32], uint32_t a0, uint32_t a1, uint32_t a2, uint32_t a3, uint64_t db) {
  asm volatile("{\n.reg .pred p;\nsetp.ne.b32 p, 1, 0;\n"
    "wgmma.mma_async.sync.aligned.m64n64k16.f32.bf16.bf16 "
    "{%0, %1, %2, %3, %4, %5, %6, %7, %8, %9, %10, %11, %12, %13, %14, %15, %16, %17, %18, %19, %20, %21, %22, %23, "
    "%24, %25, %26, %27, %28, %29, %30, %31}, "
    "{%32, %33, %34, %35}, %36, p, 1, 1, %37;\n}\n"
    : "+f"(d[0]), "+f"(d[1]), "+f"(d[2]), "+f"(d[3]), "+f"(d[4]), "+f"(d[5]), "+f"(d[6]), "+f"(d[7]), "+f"(d[8]), "+f"(d[9]), "+f"(d[10]), "+f"(d[11]),
      "+f"(d[12]), "+f"(d[13]), "+f"(d[14]), "+f"(d[15]), "+f"(d[16]), "+f"(d[17]), "+f"(d[18]), "+f"(d[19]), "+f"(d[20]), "+f"(d[21]), "+f"(d[22]), "+f"(d[23]),
      "+f"(d[24]), "+f"(d[25]), "+f"(d[26]), "+f"(d[27]), "+f"(d[28]), "+f"(d[29]), "+f"(d[30]), "+f"(d[31])
    : "r"(a0), "r"(a1), "r"(a2), "r"(a3), "l"(db), "n"(TB));
}
template<int TB> __device__ __forceinline__ void wgmma_n64_rs_z(float (&d)[32], uint32_t a0, uint32_t a1, uint32_t a2, uint32_t a3, uint64_t db) {
  asm volatile("{\n.reg .pred p;\nsetp.ne.b32 p, 0, 0;\n"
    "wgmma.mma_async.sync.aligned.m64n64k16.f32.bf16.bf16 "
    "{%0, %1, %2, %3, %4, %5, %6, %7, %8, %9, %10, %11, %12, %13, %14, %15, %16, %17, %18, %19, %20, %21, %22, %23, "
    "%24, %25, %26, %27, %28, %29, %30, %31}, "
    "{%32, %33, %34, %35}, %36, p, 1, 1, %37;\n}\n"
    : "=f"(d[0]), "=f"(d[1]), "=f"(d[2]), "=f"(d[3]), "=f"(d[4]), "=f"(d[5]), "=f"(d[6]), "=f"(d[7]), "=f"(d[8]), "=f"(d[9]), "=f"(d[10]), "=f"(d[11]),
      "=f"(d[12]), "=f"(d[13]), "=f"(d[14]), "=f"(d[15]), "=f"(d[16]), "=f"(d[17]), "=f"(d[18]), "=f"(d[19]), "=f"(d[20]), "=f"(d[21]), "=f"(d[22]), "=f"(d[23]),
      "=f"(d[24]), "=f"(d[25]), "=f"(d[26]), "=f"(d[27]), "=f"(d[28]), "=f"(d[29]), "=f"(d[30]), "=f"(d[31])
    : "r"(a0), "r"(a1), "r"(a2), "r"(a3), "l"(db), "n"(TB));
}
template<int TB> __device__ __forceinline__ void wgmma_n24_rs(float (&d)[12], uint32_t a0, uint32_t a1, uint32_t a2, uint32_t a3, uint64_t db) {
  asm volatile("{\n.reg .pred p;\nsetp.ne.b32 p, 1, 0;\n"
    "wgmma.mma_async.sync.aligned.m64n24k16.f32.bf16.bf16 "
    "{%0, %1, %2, %3, %4, %5, %6, %7, %8, %9, %10, %11}, "
    "{%12, %13, %14, %15}, %16, p, 1, 1, %17;\n}\n"
    : "+f"(d[0]), "+f"(d[1]), "+f"(d[2]), "+f"(d[3]), "+f"(d[4]), "+f"(d[5]), "+f"(d[6]), "+f"(d[7]), "+f"(d[8]), "+f"(d[9]), "+f"(d[10]), "+f"(d[11])
    : "r"(a0), "r"(a1), "r"(a2), "r"(a3), "l"(db), "n"(TB));
}

constexpr int K1_ST = 4, K1_A = 16384, K1_B = 32768, K1_STAGE = K1_A + K1_B;
constexpr int K1_SMEM = K1_ST * K1_STAGE + 8192;

__global__ void __launch_bounds__(384, 1)
k1_qkv(const __grid_constant__ CUtensorMap tmX, const __grid_constant__ CUtensorMap tmW,
       const __nv_bfloat16* __restrict__ x, const __nv_bfloat16* __restrict__ wqkv, const __nv_bfloat16* __restrict__ wo,
       const __nv_bfloat16* __restrict__ wg, const __nv_bfloat16* __restrict__ wu, const __nv_bfloat16* __restrict__ wd) {
  extern __shared__ __align__(1024) uint8_t sm[];
  float* s_cs = (float*)(sm + K1_ST * K1_STAGE);
  float2* s_st = (float2*)(s_cs + 256);
  float* s_part = (float*)(s_st + 128);
  uint64_t* s_bar = (uint64_t*)(s_part + 768);
  const uint32_t sbase = smem_u32(sm), bfull = smem_u32(s_bar), bempty = bfull + 8 * K1_ST, bside = bempty + 8 * K1_ST;
  const int tid = threadIdx.x, warp = tid >> 5, lane = tid & 31;
  const int bi = blockIdx.x >> 3, bj = blockIdx.x & 7;
  if (tid == 0) {
    for (int s = 0; s < K1_ST; s++) { mbar_init(bfull + 8 * s, 1); mbar_init(bempty + 8 * s, 2); }
    mbar_init(bside, 96);
    asm volatile("fence.mbarrier_init.release.cluster;" ::: "memory");
    asm volatile("griddepcontrol.launch_dependents;");
  }
  __syncthreads();
  if (warp == 8) {
    if (elect_one()) {
      for (int kb = 0; kb < 10; kb++) {
        const int s = kb & 3;
        if (kb >= K1_ST) mbar_wait(bempty + 8 * s, ((kb >> 2) - 1) & 1);
        const uint32_t st = sbase + s * K1_STAGE, fb = bfull + 8 * s;
        mbar_expect(fb, K1_STAGE);
        tma2d(st, &tmX, kb * 64, bi * 128, fb);
#pragma unroll
        for (int b = 0; b < 4; b++) tma2d(st + K1_A + b * 8192, &tmW, bj * 240 + b * 64, kb * 64, fb);
      }
    }
  } else if (warp > 8) {
    const int sw = warp - 9, t = tid - 288;
    {
      uint4 wv[14];
      const int k0 = bi * 40 + sw * 13 + (sw > 0), nk = sw == 0 ? 14 : 13;
      const uint4* wp = (const uint4*)(wqkv + (size_t)k0 * 1920 + bj * 240) + lane;
#pragma unroll
      for (int r = 0; r < 14; r++) wv[r] = (lane < 30 && r < nk) ? __ldg(wp + r * 240) : make_uint4(0, 0, 0, 0);
      uint2 xv[6][5];
#pragma unroll
      for (int r = 0; r < 6; r++) {
        const int row = min(sw + 3 * r, 15);
        const uint2* xp = (const uint2*)(x + (size_t)(bi * 128 + bj * 16 + row) * D_) + lane;
#pragma unroll
        for (int c = 0; c < 5; c++) xv[r][c] = __ldg(xp + c * 32);
      }
      float a[8];
#pragma unroll
      for (int e = 0; e < 8; e++) a[e] = 0.f;
#pragma unroll
      for (int r = 0; r < 14; r++) {
        a[0] += bflo(wv[r].x); a[1] += bfhi(wv[r].x); a[2] += bflo(wv[r].y); a[3] += bfhi(wv[r].y);
        a[4] += bflo(wv[r].z); a[5] += bfhi(wv[r].z); a[6] += bflo(wv[r].w); a[7] += bfhi(wv[r].w);
      }
      if (lane < 30) {
        *(float4*)(s_part + sw * 240 + lane * 8) = make_float4(a[0], a[1], a[2], a[3]);
        *(float4*)(s_part + sw * 240 + lane * 8 + 4) = make_float4(a[4], a[5], a[6], a[7]);
      }
#pragma unroll
      for (int r = 0; r < 6; r++) {
        float sum = 0.f;
#pragma unroll
        for (int c = 0; c < 5; c++) sum += (bflo(xv[r][c].x) + bfhi(xv[r][c].x)) + (bflo(xv[r][c].y) + bfhi(xv[r][c].y));
#pragma unroll
        for (int o = 16; o; o >>= 1) sum += __shfl_xor_sync(0xffffffffu, sum, o);
        const float mean = sum * (1.f / D_);
        float q = 0.f;
#pragma unroll
        for (int c = 0; c < 5; c++) {
          float d0 = bflo(xv[r][c].x) - mean, d1 = bfhi(xv[r][c].x) - mean, d2 = bflo(xv[r][c].y) - mean, d3 = bfhi(xv[r][c].y) - mean;
          q += d0 * d0 + d1 * d1 + d2 * d2 + d3 * d3;
        }
#pragma unroll
        for (int o = 16; o; o >>= 1) q += __shfl_xor_sync(0xffffffffu, q, o);
        if (lane == 0 && sw + 3 * r < 16) g_st1[bi * 128 + bj * 16 + sw + 3 * r] = make_float2(mean, rsqrtf(q * (1.f / D_) + LN_EPS));
      }
      bar_sync(1, 96);
      if (t < 60) {
        float4 p0 = *(float4*)(s_part + t * 4), p1 = *(float4*)(s_part + 240 + t * 4), p2 = *(float4*)(s_part + 480 + t * 4);
        *(float4*)(g_cs1 + bi * 1920 + bj * 240 + t * 4) = make_float4(p0.x + p1.x + p2.x, p0.y + p1.y + p2.y, p0.z + p1.z + p2.z, p0.w + p1.w + p2.w);
      }
      bar_sync(1, 96);
      if (t == 0) { flag_add(g_flags + (FL_ROW + bi) * 32); flag_add(g_flags + (FL_COL + bj) * 32); }
    }
    {
      const int ch = t % 48, half = t / 48;
      const __nv_bfloat16* src = (ch < 24 ? wg + ch * 8 : wu + (ch - 24) * 8) + bj * 192 + (size_t)(bi * 40 + half * 20) * F_;
      uint4 wv[20];
#pragma unroll
      for (int r = 0; r < 20; r++) wv[r] = __ldg((const uint4*)(src + (size_t)r * F_));
      float a[8];
#pragma unroll
      for (int e = 0; e < 8; e++) a[e] = 0.f;
#pragma unroll
      for (int r = 0; r < 20; r++) {
        a[0] += bflo(wv[r].x); a[1] += bfhi(wv[r].x); a[2] += bflo(wv[r].y); a[3] += bfhi(wv[r].y);
        a[4] += bflo(wv[r].z); a[5] += bfhi(wv[r].z); a[6] += bflo(wv[r].w); a[7] += bfhi(wv[r].w);
      }
      *(float4*)(s_part + half * 384 + ch * 8) = make_float4(a[0], a[1], a[2], a[3]);
      *(float4*)(s_part + half * 384 + ch * 8 + 4) = make_float4(a[4], a[5], a[6], a[7]);
      if (t == 0) { flag_wait(g_flags + (FL_ROW + bi) * 32, 8); flag_wait(g_flags + (FL_COL + bj) * 32, 16); }
      bar_sync(1, 96);
      float4 p0 = *(float4*)(s_part + t * 4), p1 = *(float4*)(s_part + 384 + t * 4);
      *(float4*)(g_cs2 + bi * 3072 + bj * 384 + t * 4) = make_float4(p0.x + p1.x, p0.y + p1.y, p0.z + p1.z, p0.w + p1.w);
    }
    if (t < 60) {
      float4 v[16];
#pragma unroll
      for (int r = 0; r < 16; r++) v[r] = __ldcg((const float4*)(g_cs1 + r * 1920 + bj * 240 + t * 4));
      float4 a = v[0];
#pragma unroll
      for (int r = 1; r < 16; r++) { a.x += v[r].x; a.y += v[r].y; a.z += v[r].z; a.w += v[r].w; }
      *(float4*)(s_cs + t * 4) = a;
    } else if (t >= 64) {
      const float4* p = (const float4*)(g_st1 + bi * 128) + (t - 64) * 2;
      float4 v0 = __ldcg(p), v1 = __ldcg(p + 1);
      ((float4*)s_st)[(t - 64) * 2] = v0; ((float4*)s_st)[(t - 64) * 2 + 1] = v1;
    }
    mbar_arrive(bside);
    {
      uint4 v[15];
#pragma unroll
      for (int r = 0; r < 15; r++) {
        const int u = t + r * 96;
        if (u < 1360) {
          const bool isd = u >= 400;
          const int idx = isd ? blockIdx.x * 960 + (u - 400) : blockIdx.x * 400 + u;
          const int blk = idx / 80, in = idx % 80, kch = isd ? 192 : 80;
          const int j = blk / kch, kc = blk % kch;
          v[r] = __ldg((const uint4*)((isd ? wd : wo) + (size_t)(kc * 8 + (in & 7)) * D_ + j * 80 + (in >> 3) * 8));
        }
      }
#pragma unroll
      for (int r = 0; r < 15; r++) {
        const int u = t + r * 96;
        if (u < 400) ((uint4*)g_wo)[blockIdx.x * 400 + u] = v[r];
        else if (u < 1360) ((uint4*)g_wd)[blockIdx.x * 960 + (u - 400)] = v[r];
      }
    }
  } else {
    const int wg = warp >> 2;
    float acc[120];
    const uint64_t da0 = mkdesc(sbase + wg * 8192, 16, 1024, 1), db0 = mkdesc(sbase + K1_A, 8192, 1024, 1);
#pragma unroll 1
    for (int kb = 0; kb < 10; kb++) {
      const int s = kb & 3;
      mbar_wait(bfull + 8 * s, (kb >> 2) & 1);
      const uint64_t da = da0 + s * (K1_STAGE >> 4), db = db0 + s * (K1_STAGE >> 4);
      WG_FENCE();
#pragma unroll
      for (int k = 0; k < 4; k++) wgmma_n240_ss<1>(acc, da + k * 2, db + k * 128, (kb | k) != 0);
      WG_COMMIT();
      WG_WAIT(1);
      if (kb > 0 && (tid & 127) == 0) mbar_arrive(bempty + 8 * ((kb - 1) & 3));
    }
    WG_WAIT(0);
    fence_f(acc);
    mbar_wait(bside, 0);
    const int rl = wg * 64 + (warp & 3) * 16 + (lane >> 2), q = lane & 3;
    const float2 st0 = s_st[rl], st1 = s_st[rl + 8];
    const bool poly0 = (POLY_MASK >> ((rl >> 3) & 15)) & 1, poly1 = (POLY_MASK >> (((rl >> 3) + 1) & 15)) & 1;
    uint8_t* ob = g_qkv + (size_t)(bi * 128 + rl) * 16;
#pragma unroll
    for (int m = 0; m < 6; m++) {
      const int hs = bj * 12 + 2 * m, ty = hs >> 5;
      const float c0 = st0.y * (ty == 0 ? 0.32259642f : (ty == 1 && poly0) ? 2.f : 1.f);
      const float c1 = st1.y * (ty == 0 ? 0.32259642f : (ty == 1 && poly1) ? 2.f : 1.f);
      const uint32_t kc = (q & 1) ? 0x0000BB73u : 0xC04B4440u;
      const uint32_t cq = (q & 1) ? 0x00003F80u : 0x3F803F80u, cv = (q & 1) ? 0u : 0x00003F80u;
      const uint32_t p0 = ty == 0 ? cq : ty == 2 ? cv : (poly0 ? kc : 0u), p1 = ty == 0 ? cq : ty == 2 ? cv : (poly1 ? kc : 0u);
      uint8_t* oa = ob + (size_t)hs * 3 * PLANE;
#pragma unroll
      for (int g = 0; g < 5; g++) {
        const int G = 5 * m + g;
        const float2 cs = *(const float2*)(s_cs + G * 8 + q * 2);
        const uint32_t v0 = packbf((acc[4 * G] - st0.x * cs.x) * c0, (acc[4 * G + 1] - st0.x * cs.y) * c0);
        const uint32_t v1 = packbf((acc[4 * G + 2] - st1.x * cs.x) * c1, (acc[4 * G + 3] - st1.x * cs.y) * c1);
        if (g != 2) {
          uint8_t* p = oa + (g < 2 ? g : g) * PLANE + q * 4;
          *(uint32_t*)p = v0; *(uint32_t*)(p + 128) = v1;
        } else {
          uint8_t* p = oa + 2 * PLANE + q * 4;
          *(uint32_t*)p = q < 2 ? v0 : p0; *(uint32_t*)(p + 128) = q < 2 ? v1 : p1;
          p = oa + 5 * PLANE + (q ^ 2) * 4;
          *(uint32_t*)p = q < 2 ? p0 : v0; *(uint32_t*)(p + 128) = q < 2 ? p1 : v1;
        }
      }
    }
  }
}

__device__ __forceinline__ uint32_t exp2_pair(float y0, float y1, uint32_t cm) {
  const uint32_t L = __byte_perm(__float_as_uint(y0), __float_as_uint(y1), 0x6521);
  uint32_t zh, E, r;
  asm("lop3.b32 %0, %1, %2, 0x3F003F00, 0xEA;" : "=r"(zh) : "r"(L), "r"(cm));
  asm("lop3.b32 %0, %1, %2, 0x00010001, 0xBA;" : "=r"(E) : "r"(L), "r"(cm));
  asm("fma.rn.bf16x2 %0, %1, %2, %3;" : "=r"(r) : "r"(L), "r"(zh), "r"(E));
  return r;
}
constexpr int K2_SMEM = 6 * PLANE + 3 * 8192 + 256;

__device__ __forceinline__ void att_store(const float (&o)[12], int h, int row, int lane) {
  const float l0 = __shfl_sync(0xffffffffu, o[8], (lane & ~3) | 2), l1 = __shfl_sync(0xffffffffu, o[10], (lane & ~3) | 2);
  const float i0 = __fdividef(1.f, l0), i1 = __fdividef(1.f, l1);
  const int q = lane & 3, odd = h & 1;
  uint8_t* p = g_o + ((size_t)(row >> 7) * 80 + (h >> 1) * 5) * 2048 + (row & 127) * 16 + q * 4;
  uint8_t* pa = p + odd * 3 * 2048;
  *(uint32_t*)(pa) = packbf(o[0] * i0, o[1] * i0);        *(uint32_t*)(pa + 128) = packbf(o[2] * i1, o[3] * i1);
  *(uint32_t*)(pa + 2048) = packbf(o[4] * i0, o[5] * i0); *(uint32_t*)(pa + 2048 + 128) = packbf(o[6] * i1, o[7] * i1);
  if (q < 2) {
    uint8_t* pb = p + 2 * 2048 + odd * 8;
    *(uint32_t*)(pb) = packbf(o[8] * i0, o[9] * i0);      *(uint32_t*)(pb + 128) = packbf(o[10] * i1, o[11] * i1);
  }
}

__global__ void __launch_bounds__(512, 1) k2_attn(uint32_t zero) {
  extern __shared__ __align__(1024) uint8_t sm[];
  uint64_t* s_bar = (uint64_t*)(sm + 6 * PLANE + 3 * 8192);
  unsigned* s_max = (unsigned*)(s_bar + 10);
  const uint32_t sK = smem_u32(sm), sV = sK + 3 * PLANE, sQ = sK + 6 * PLANE, bars = smem_u32(s_bar);
  const int tid = threadIdx.x, wid = tid >> 5, lane = tid & 31, wg = tid >> 7;
  const int h = blockIdx.x >> 2, quarter = blockIdx.x & 3;
  if (tid == 0) {
    for (int i = 0; i < 9; i++) mbar_init(bars + 8 * i, 1);
    s_max[0] = 0; s_max[1] = 0;
    asm volatile("fence.mbarrier_init.release.cluster;" ::: "memory");
  }
  __syncthreads();
  asm volatile("griddepcontrol.wait;" ::: "memory");
  if (wid < 9 && elect_one()) {
    const uint32_t b = bars + 8 * wid;
    if (wid < 8) {
      const uint8_t* kp = g_qkv + (size_t)(32 + h) * 3 * PLANE + wid * 4096;
      const uint8_t* vp = g_qkv + (size_t)(64 + h) * 3 * PLANE + wid * 4096;
      mbar_expect(b, 6 * 4096);
#pragma unroll
      for (int c = 0; c < 3; c++) bulk_g2s(sK + c * PLANE + wid * 4096, kp + c * PLANE, 4096, b);
#pragma unroll
      for (int c = 0; c < 3; c++) bulk_g2s(sV + c * PLANE + wid * 4096, vp + c * PLANE, 4096, b);
    } else {
      mbar_expect(b, 3 * 8192);
#pragma unroll
      for (int c = 0; c < 3; c++) bulk_g2s(sQ + c * 8192, g_qkv + ((size_t)h * 3 + c) * PLANE + quarter * 8192, 8192, b);
      asm volatile("griddepcontrol.launch_dependents;");
    }
  }
  if (blockIdx.x == 0 && tid >= 448 && tid - 448 < FL_N) g_flags[(tid - 448) * 32] = 0;
  __syncwarp();
  const uint32_t cm = 0x007F007Fu | zero;
  const uint64_t dk0 = mkdesc(sK, PLANE, 128, 0), dv0 = mkdesc(sV, 128, PLANE, 0);
  mbar_wait(bars + 64, 0);
#pragma unroll 1
  for (int pass = 0; pass < 2; pass++) {
    const int rl = (pass * 4 + wg) * 64 + (wid & 3) * 16 + (lane >> 2);
    uint32_t q[8];
    {
      const uint8_t* qp = sm + 6 * PLANE + rl * 16 + (lane & 3) * 4;
      q[0] = *(const uint32_t*)(qp); q[1] = *(const uint32_t*)(qp + 128);
      q[2] = *(const uint32_t*)(qp + 8192); q[3] = *(const uint32_t*)(qp + 8192 + 128);
      q[4] = *(const uint32_t*)(qp + 16384); q[5] = *(const uint32_t*)(qp + 16384 + 128);
      q[6] = q[0] & zero; q[7] = q[1] & zero;
    }
    fence_u(q);
    float o[12];
#pragma unroll
    for (int i = 0; i < 12; i++) o[i] = 0.f;
    fence_f(o);
    uint64_t dk = dk0, dv = dv0;
#pragma unroll 1
    for (int j = 0; j < 8; j++) {
      if (pass == 0) mbar_wait(bars + 8 * j, 0);
#pragma unroll
      for (int u = 0; u < 2; u++) {
        float s[64]; uint32_t p[32];
        WG_FENCE();
        wgmma_n128_rs_z<0>(s, q[0], q[1], q[2], q[3], dk + u * 128);
        wgmma_n128_rs<0>(s, q[4], q[5], q[6], q[7], dk + u * 128 + (2 * PLANE >> 4));
        WG_COMMIT();
        WG_WAIT(0);
        fence_f(s);
#pragma unroll
        for (int g = 0; g < 16; g++) {
          if ((POLY_MASK >> g) & 1) {
            p[2 * g] = exp2_pair(s[4 * g], s[4 * g + 1], cm);
            p[2 * g + 1] = exp2_pair(s[4 * g + 2], s[4 * g + 3], cm);
          } else {
            p[2 * g] = packbf(ex2f(s[4 * g]), ex2f(s[4 * g + 1]));
            p[2 * g + 1] = packbf(ex2f(s[4 * g + 2]), ex2f(s[4 * g + 3]));
          }
        }
        fence_u(p);
        WG_FENCE();
#pragma unroll
        for (int c = 0; c < 8; c++) wgmma_n24_rs<1>(o, p[4 * c], p[4 * c + 1], p[4 * c + 2], p[4 * c + 3], dv + u * 128 + c * 16);
        WG_COMMIT();
        WG_WAIT(0);
      }
      dk += 256; dv += 256;
    }
    fence_f(o);
    att_store(o, h, quarter * 512 + rl, lane);
    if (pass == 0) {
      float km = 0.f;
#pragma unroll
      for (int r = 0; r < 5; r++) {
        const uint8_t* p = r < 4 ? sm + (wid * 128 + r * 32 + lane) * 16 : sm + 6 * PLANE + (wid * 32 + lane) * 16;
        const int st = r < 4 ? PLANE : 8192;
        const uint4 a = *(const uint4*)p, b = *(const uint4*)(p + st);
        const uint2 c = *(const uint2*)(p + 2 * st);
        const uint32_t w[10] = {a.x, a.y, a.z, a.w, b.x, b.y, b.z, b.w, c.x, c.y};
        float n = 0.f;
#pragma unroll
        for (int e = 0; e < 10; e++) { n = fmaf(bflo(w[e]), bflo(w[e]), n); n = fmaf(bfhi(w[e]), bfhi(w[e]), n); }
        if (r < 4) {
          if ((POLY_MASK >> ((r * 4 + (lane >> 3)) & 15)) & 1) n *= 0.25f;
          km = __uint_as_float(max(__float_as_uint(km), __float_as_uint(n)));
        } else {
          const unsigned a0 = __reduce_max_sync(0xffffffffu, __float_as_uint(n)), a1 = __reduce_max_sync(0xffffffffu, __float_as_uint(km));
          if (lane == 0) { atomicMax(s_max, a0); atomicMax(s_max + 1, a1); }
        }
      }
    }
  }
  __syncthreads();
  if (!(__uint_as_float(s_max[0]) * __uint_as_float(s_max[1]) <= 4096.f)) {
#pragma unroll 1
    for (int pass = 0; pass < 2; pass++) {
      const int rl = (pass * 4 + wg) * 64 + (wid & 3) * 16 + (lane >> 2);
      uint32_t q[8];
      const uint8_t* qp = sm + 6 * PLANE + rl * 16 + (lane & 3) * 4;
      q[0] = *(const uint32_t*)(qp); q[1] = *(const uint32_t*)(qp + 128);
      q[2] = *(const uint32_t*)(qp + 8192); q[3] = *(const uint32_t*)(qp + 8192 + 128);
      q[4] = *(const uint32_t*)(qp + 16384); q[5] = *(const uint32_t*)(qp + 16384 + 128);
      if (lane & 2) { q[4] = 0; q[5] = 0; }
      q[6] = q[0] & zero; q[7] = q[1] & zero;
      fence_u(q);
      float o[12];
#pragma unroll
      for (int i = 0; i < 12; i++) o[i] = 0.f;
      float m0 = -INFINITY, m1 = -INFINITY;
#pragma unroll 1
      for (int j = 0; j < 16; j++) {
        float s[64]; uint32_t p[32];
        WG_FENCE();
        wgmma_n128_rs_z<0>(s, q[0], q[1], q[2], q[3], dk0 + j * 128);
        wgmma_n128_rs<0>(s, q[4], q[5], q[6], q[7], dk0 + j * 128 + (2 * PLANE >> 4));
        WG_COMMIT();
        WG_WAIT(0);
        fence_f(s);
        float n0 = m0, n1 = m1;
#pragma unroll
        for (int g = 0; g < 16; g++) {
          if ((POLY_MASK >> g) & 1) { s[4 * g] *= 0.5f; s[4 * g + 1] *= 0.5f; s[4 * g + 2] *= 0.5f; s[4 * g + 3] *= 0.5f; }
          n0 = fmaxf(n0, fmaxf(s[4 * g], s[4 * g + 1])); n1 = fmaxf(n1, fmaxf(s[4 * g + 2], s[4 * g + 3]));
        }
        n0 = fmaxf(n0, __shfl_xor_sync(0xffffffffu, n0, 1)); n0 = fmaxf(n0, __shfl_xor_sync(0xffffffffu, n0, 2));
        n1 = fmaxf(n1, __shfl_xor_sync(0xffffffffu, n1, 1)); n1 = fmaxf(n1, __shfl_xor_sync(0xffffffffu, n1, 2));
        const float a0 = ex2f(m0 - n0), a1 = ex2f(m1 - n1);
        m0 = n0; m1 = n1;
#pragma unroll
        for (int i = 0; i < 3; i++) { o[4 * i] *= a0; o[4 * i + 1] *= a0; o[4 * i + 2] *= a1; o[4 * i + 3] *= a1; }
#pragma unroll
        for (int g = 0; g < 16; g++) {
          p[2 * g] = packbf(ex2f(s[4 * g] - m0), ex2f(s[4 * g + 1] - m0));
          p[2 * g + 1] = packbf(ex2f(s[4 * g + 2] - m1), ex2f(s[4 * g + 3] - m1));
        }
        fence_u(p); fence_f(o);
        WG_FENCE();
#pragma unroll
        for (int c = 0; c < 8; c++) wgmma_n24_rs<1>(o, p[4 * c], p[4 * c + 1], p[4 * c + 2], p[4 * c + 3], dv0 + j * 128 + c * 16);
        WG_COMMIT();
        WG_WAIT(0);
        fence_f(o);
      }
      att_store(o, h, quarter * 512 + rl, lane);
    }
  }
}

constexpr int CE_ST = 7, CE_STAGE = 16384 + 10240, D_ST = 3, D_STAGE = 65536;
constexpr int K3_RING = D_ST * D_STAGE;
constexpr int K3_SMEM = K3_RING + 20480 + 4096;

__global__ void __launch_bounds__(384, 1)
k3_ffn(const __grid_constant__ CUtensorMap tmG, const __grid_constant__ CUtensorMap tmU,
       const __nv_bfloat16* __restrict__ x, __nv_bfloat16* __restrict__ out) {
  extern __shared__ __align__(1024) uint8_t sm[];
  uint32_t* s_h = (uint32_t*)(sm + K3_RING);
  float* s_cs = (float*)(sm + K3_RING + 20480);
  float2* s_st = (float2*)(s_cs + 384);
  uint64_t* s_bar = (uint64_t*)(s_st + 128);
  const uint32_t sbase = smem_u32(sm), b0 = smem_u32(s_bar);
  const uint32_t cfull = b0, cempty = b0 + 56, efull = b0 + 112, eempty = b0 + 168, dfull = b0 + 224, dempty = b0 + 248,
                 cdone = b0 + 272, ddone = b0 + 280, bside = b0 + 288;
  const int tid = threadIdx.x, warp = tid >> 5, lane = tid & 31;
  const int bi = blockIdx.x >> 3, bj = blockIdx.x & 7;
  if (tid == 0) {
    for (int s = 0; s < CE_ST; s++) { mbar_init(cfull + 8 * s, 1); mbar_init(cempty + 8 * s, 2); mbar_init(efull + 8 * s, 1); mbar_init(eempty + 8 * s, 2); }
    for (int s = 0; s < D_ST; s++) { mbar_init(dfull + 8 * s, 1); mbar_init(dempty + 8 * s, 2); }
    mbar_init(cdone, 2); mbar_init(ddone, 2); mbar_init(bside, 96);
    asm volatile("fence.mbarrier_init.release.cluster;" ::: "memory");
  }
  __syncthreads();
  if (warp >= 8) {
    asm volatile("setmaxnreg.dec.sync.aligned.u32 40;");
    if (warp == 8) {
      if (elect_one()) {
        const uint8_t* wsrc = g_wo + bj * 80 * 1280;
        for (int s = 0; s < CE_ST; s++) {
          mbar_expect(cfull + 8 * s, CE_STAGE);
          bulk_g2s(sbase + s * CE_STAGE + 16384, wsrc + s * 10240, 10240, cfull + 8 * s);
        }
        asm volatile("griddepcontrol.wait;" ::: "memory");
        const uint8_t* asrc = g_o + bi * 80 * 2048;
        for (int kb = 0; kb < 10; kb++) {
          const int s = kb < CE_ST ? kb : kb - CE_ST;
          if (kb >= CE_ST) {
            mbar_wait(cempty + 8 * s, 0);
            mbar_expect(cfull + 8 * s, CE_STAGE);
            bulk_g2s(sbase + s * CE_STAGE + 16384, wsrc + kb * 10240, 10240, cfull + 8 * s);
          }
          bulk_g2s(sbase + s * CE_STAGE, asrc + kb * 16384, 16384, cfull + 8 * s);
        }
        mbar_wait(cdone, 0);
        for (int s = 0; s < D_ST; s++) {
          mbar_expect(dfull + 8 * s, D_STAGE);
          tma3d(sbase + s * D_STAGE + 16384, &tmG, 0, s * 64, bj * 3, dfull + 8 * s);
          tma3d(sbase + s * D_STAGE + 16384 + 24576, &tmU, 0, s * 64, bj * 3, dfull + 8 * s);
        }
        flag_wait(g_flags + (FL_C + bi) * 32, 8);
        asm volatile("fence.proxy.async;" ::: "memory");
        asrc = g_h + bi * 80 * 2048;
        {
          int s = 0, ph = 1;
          for (int kb = 0; kb < 10; kb++) {
            if (kb >= D_ST) {
              mbar_wait(dempty + 8 * s, ph);
              mbar_expect(dfull + 8 * s, D_STAGE);
              tma3d(sbase + s * D_STAGE + 16384, &tmG, 0, kb * 64, bj * 3, dfull + 8 * s);
              tma3d(sbase + s * D_STAGE + 16384 + 24576, &tmU, 0, kb * 64, bj * 3, dfull + 8 * s);
            }
            bulk_g2s(sbase + s * D_STAGE, asrc + kb * 16384, 16384, dfull + 8 * s);
            if (++s == D_ST) { s = 0; ph ^= 1; }
          }
        }
        mbar_wait(ddone, 0);
        wsrc = g_wd + bj * 192 * 1280;
        for (int s = 0; s < CE_ST; s++) {
          mbar_expect(efull + 8 * s, CE_STAGE);
          bulk_g2s(sbase + s * CE_STAGE + 16384, wsrc + s * 10240, 10240, efull + 8 * s);
        }
        flag_wait(g_flags + (FL_D + bi) * 32, 8);
        asm volatile("fence.proxy.async;" ::: "memory");
        asrc = g_H + bi * 192 * 2048;
        {
          int s = 0, ph = 1;
          for (int kb = 0; kb < 24; kb++) {
            if (kb >= CE_ST) {
              mbar_wait(eempty + 8 * s, ph);
              mbar_expect(efull + 8 * s, CE_STAGE);
              bulk_g2s(sbase + s * CE_STAGE + 16384, wsrc + kb * 10240, 10240, efull + 8 * s);
            }
            bulk_g2s(sbase + s * CE_STAGE, asrc + kb * 16384, 16384, efull + 8 * s);
            if (++s == CE_ST) { s = 0; ph ^= 1; }
          }
        }
      }
    } else {
      const int t = tid - 288;
      asm volatile("griddepcontrol.wait;" ::: "memory");
      float4 a = make_float4(0.f, 0.f, 0.f, 0.f);
#pragma unroll 4
      for (int r = 0; r < 16; r++) {
        const float4 v = __ldcg((const float4*)(g_cs2 + r * 3072 + bj * 384 + t * 4));
        a.x += v.x; a.y += v.y; a.z += v.z; a.w += v.w;
      }
      *(float4*)(s_cs + t * 4) = a;
      if (lane == 0) flag_wait(g_flags + (FL_C + bi) * 32, 8);
      __syncwarp();
      for (int r = t; r < 128; r += 96) {
        const float4* p = (const float4*)(g_st2 + (bi * 128 + r) * 8);
        const float4 v0 = __ldcg(p), v1 = __ldcg(p + 1), v2 = __ldcg(p + 2), v3 = __ldcg(p + 3);
        const float mean = (((v0.x + v0.z) + (v1.x + v1.z)) + ((v2.x + v2.z) + (v3.x + v3.z))) * 0.125f;
        const float m2 = ((v0.y + v0.w) + (v1.y + v1.w)) + ((v2.y + v2.w) + (v3.y + v3.w));
        float d = 0.f, e;
        e = v0.x - mean; d += e * e; e = v0.z - mean; d += e * e; e = v1.x - mean; d += e * e; e = v1.z - mean; d += e * e;
        e = v2.x - mean; d += e * e; e = v2.z - mean; d += e * e; e = v3.x - mean; d += e * e; e = v3.z - mean; d += e * e;
        s_st[r] = make_float2(mean, rsqrtf((m2 + 80.f * d) * (1.f / D_) + LN_EPS));
      }
      mbar_arrive(bside);
    }
  } else {
    asm volatile("setmaxnreg.inc.sync.aligned.u32 232;");
    const int wg = warp >> 2, q = lane & 3;
    const int rl = wg * 64 + (warp & 3) * 16 + (lane >> 2);
    const uint64_t da0 = mkdesc(sbase + wg * 1024, 2048, 128, 0), db0 = mkdesc(sbase + 16384, 1280, 128, 0);
    {
      uint32_t xr[20];
      const uint32_t* xp = (const uint32_t*)(x + (size_t)(bi * 128 + rl) * D_ + bj * 80) + q;
#pragma unroll
      for (int g = 0; g < 10; g++) { xr[2 * g] = __ldg(xp + g * 4); xr[2 * g + 1] = __ldg(xp + g * 4 + 8 * D_ / 2); }
      float acc[40];
#pragma unroll 1
      for (int kb = 0; kb < 10; kb++) {
        const int s = kb < CE_ST ? kb : kb - CE_ST;
        mbar_wait(cfull + 8 * s, kb >= CE_ST);
        const uint64_t da = da0 + s * (CE_STAGE >> 4), db = db0 + s * (CE_STAGE >> 4);
        WG_FENCE();
#pragma unroll
        for (int k = 0; k < 4; k++) wgmma_n80_ss<1>(acc, da + k * 256, db + k * 160, (kb | k) != 0);
        WG_COMMIT();
        WG_WAIT(1);
        if (kb > 0 && kb <= 3 && (tid & 127) == 0) mbar_arrive(cempty + 8 * (kb - 1));
      }
      WG_WAIT(0);
      fence_f(acc);
      if ((tid & 127) == 0) mbar_arrive(cdone);
      uint8_t* hp = g_h + ((size_t)bi * 80 + bj * 10) * 2048 + rl * 16 + q * 4;
      float s0 = 0.f, s1 = 0.f;
#pragma unroll
      for (int g = 0; g < 10; g++) {
        const uint32_t v0 = packbf(acc[4 * g] + bflo(xr[2 * g]), acc[4 * g + 1] + bfhi(xr[2 * g]));
        const uint32_t v1 = packbf(acc[4 * g + 2] + bflo(xr[2 * g + 1]), acc[4 * g + 3] + bfhi(xr[2 * g + 1]));
        *(uint32_t*)(hp + g * 2048) = v0; *(uint32_t*)(hp + g * 2048 + 128) = v1;
        s_h[(2 * g) * 256 + tid] = v0; s_h[(2 * g + 1) * 256 + tid] = v1;
        acc[4 * g] = bflo(v0); acc[4 * g + 1] = bfhi(v0); acc[4 * g + 2] = bflo(v1); acc[4 * g + 3] = bfhi(v1);
        s0 += acc[4 * g] + acc[4 * g + 1]; s1 += acc[4 * g + 2] + acc[4 * g + 3];
      }
      s0 += __shfl_xor_sync(0xffffffffu, s0, 1); s1 += __shfl_xor_sync(0xffffffffu, s1, 1);
      s0 += __shfl_xor_sync(0xffffffffu, s0, 2); s1 += __shfl_xor_sync(0xffffffffu, s1, 2);
      s0 *= (1.f / 80.f); s1 *= (1.f / 80.f);
      float q0 = 0.f, q1 = 0.f;
#pragma unroll
      for (int g = 0; g < 10; g++) {
        float d;
        d = acc[4 * g] - s0; q0 += d * d; d = acc[4 * g + 1] - s0; q0 += d * d;
        d = acc[4 * g + 2] - s1; q1 += d * d; d = acc[4 * g + 3] - s1; q1 += d * d;
      }
      q0 += __shfl_xor_sync(0xffffffffu, q0, 1); q1 += __shfl_xor_sync(0xffffffffu, q1, 1);
      q0 += __shfl_xor_sync(0xffffffffu, q0, 2); q1 += __shfl_xor_sync(0xffffffffu, q1, 2);
      if (q == 0) g_st2[(bi * 128 + rl) * 8 + bj] = make_float2(s0, q0);
      if (q == 1) g_st2[(bi * 128 + rl + 8) * 8 + bj] = make_float2(s1, q1);
      asm volatile("fence.proxy.async;" ::: "memory");
      bar_sync(1, 256);
      if (tid == 0) flag_add(g_flags + (FL_C + bi) * 32);
    }
    {
      float ag[96], au[96];
      const uint64_t dbg = mkdesc(sbase + 16384, 8192, 1024, 1);
      int s = 0, ph = 0;
#pragma unroll 1
      for (int kb = 0; kb < 10; kb++) {
        mbar_wait(dfull + 8 * s, ph);
        const uint64_t da = da0 + s * (D_STAGE >> 4), db = dbg + s * (D_STAGE >> 4);
        WG_FENCE();
#pragma unroll
        for (int k = 0; k < 4; k++) {
          wgmma_n192_ss<1>(ag, da + k * 256, db + k * 128, (kb | k) != 0);
          wgmma_n192_ss<1>(au, da + k * 256, db + k * 128 + (24576 >> 4), (kb | k) != 0);
        }
        WG_COMMIT();
        WG_WAIT(1);
        if (kb > 0 && (tid & 127) == 0) mbar_arrive(dempty + 8 * (s == 0 ? D_ST - 1 : s - 1));
        if (++s == D_ST) { s = 0; ph ^= 1; }
      }
      WG_WAIT(0);
      fence_f(ag); fence_f(au);
      if ((tid & 127) == 0) mbar_arrive(ddone);
      mbar_wait(bside, 0);
      const float2 st0 = s_st[rl], st1 = s_st[rl + 8];
      uint8_t* hp = g_H + ((size_t)bi * 192 + bj * 24) * 2048 + rl * 16 + q * 4;
#pragma unroll
      for (int g = 0; g < 24; g++) {
        const float2 cg = *(const float2*)(s_cs + g * 8 + q * 2), cu = *(const float2*)(s_cs + 192 + g * 8 + q * 2);
        float r[4];
#pragma unroll
        for (int e = 0; e < 4; e++) {
          const float2 st = e < 2 ? st0 : st1;
          const float gv = (ag[4 * g + e] - st.x * ((e & 1) ? cg.y : cg.x)) * st.y;
          const float uv = (au[4 * g + e] - st.x * ((e & 1) ? cu.y : cu.x)) * (0.5f * st.y);
          const float th = tanhf_(gv * fmaf(gv * gv, 0.035677408f, 0.79788456f));
          const float hv = gv * uv;
          r[e] = fmaf(hv, th, hv);
        }
        *(uint32_t*)(hp + g * 2048) = packbf(r[0], r[1]);
        *(uint32_t*)(hp + g * 2048 + 128) = packbf(r[2], r[3]);
      }
      asm volatile("fence.proxy.async;" ::: "memory");
      bar_sync(1, 256);
      if (tid == 0) flag_add(g_flags + (FL_D + bi) * 32);
    }
    {
      float acc[40];
      int s = 0, ph = 0;
#pragma unroll 1
      for (int kb = 0; kb < 24; kb++) {
        mbar_wait(efull + 8 * s, ph);
        const uint64_t da = da0 + s * (CE_STAGE >> 4), db = db0 + s * (CE_STAGE >> 4);
        WG_FENCE();
#pragma unroll
        for (int k = 0; k < 4; k++) wgmma_n80_ss<1>(acc, da + k * 256, db + k * 160, (kb | k) != 0);
        WG_COMMIT();
        WG_WAIT(1);
        if (kb > 0 && (tid & 127) == 0) mbar_arrive(eempty + 8 * (s == 0 ? CE_ST - 1 : s - 1));
        if (++s == CE_ST) { s = 0; ph ^= 1; }
      }
      WG_WAIT(0);
      fence_f(acc);
      uint32_t* op = (uint32_t*)(out + (size_t)(bi * 128 + rl) * D_ + bj * 80) + q;
#pragma unroll
      for (int g = 0; g < 10; g++) {
        const uint32_t h0 = s_h[(2 * g) * 256 + tid], h1 = s_h[(2 * g + 1) * 256 + tid];
        op[g * 4] = packbf(acc[4 * g] + bflo(h0), acc[4 * g + 1] + bfhi(h0));
        op[g * 4 + 8 * D_ / 2] = packbf(acc[4 * g + 2] + bflo(h1), acc[4 * g + 3] + bfhi(h1));
      }
    }
  }
}

typedef CUresult (*EncodeFn)(CUtensorMap*, CUtensorMapDataType, cuuint32_t, void*, const cuuint64_t*, const cuuint64_t*, const cuuint32_t*,
                             const cuuint32_t*, CUtensorMapInterleave, CUtensorMapSwizzle, CUtensorMapL2promotion, CUtensorMapFloatOOBfill);

}

extern "C" void kernel_launch(void* const* d_in, const int* in_sizes, int n_in, void* d_out, int out_size) {
  const __nv_bfloat16* x = (const __nv_bfloat16*)d_in[0];
  const __nv_bfloat16* wqkv = (const __nv_bfloat16*)d_in[1];
  const __nv_bfloat16* wo = (const __nv_bfloat16*)d_in[2];
  const __nv_bfloat16* wg = (const __nv_bfloat16*)d_in[4];
  const __nv_bfloat16* wu = (const __nv_bfloat16*)d_in[5];
  const __nv_bfloat16* wd = (const __nv_bfloat16*)d_in[6];
  static EncodeFn enc = nullptr;
  if (!enc) {
    void* fn = nullptr;
    cudaDriverEntryPointQueryResult qr;
    cudaGetDriverEntryPoint("cuTensorMapEncodeTiled", &fn, cudaEnableDefault, &qr);
    enc = (EncodeFn)fn;
    cudaFuncSetAttribute(k1_qkv, cudaFuncAttributeMaxDynamicSharedMemorySize, K1_SMEM);
    cudaFuncSetAttribute(k2_attn, cudaFuncAttributeMaxDynamicSharedMemorySize, K2_SMEM);
    cudaFuncSetAttribute(k3_ffn, cudaFuncAttributeMaxDynamicSharedMemorySize, K3_SMEM);
  }
  CUtensorMap tmX, tmW, tmG, tmU;
  const cuuint32_t es[3] = {1, 1, 1};
  {
    cuuint64_t gd[2] = {640, 2048}, gs[1] = {1280};
    cuuint32_t bd[2] = {64, 128};
    enc(&tmX, CU_TENSOR_MAP_DATA_TYPE_BFLOAT16, 2, (void*)x, gd, gs, bd, es, CU_TENSOR_MAP_INTERLEAVE_NONE, CU_TENSOR_MAP_SWIZZLE_128B, CU_TENSOR_MAP_L2_PROMOTION_L2_128B, CU_TENSOR_MAP_FLOAT_OOB_FILL_NONE);
  }
  {
    cuuint64_t gd[2] = {1920, 640}, gs[1] = {3840};
    cuuint32_t bd[2] = {64, 64};
    enc(&tmW, CU_TENSOR_MAP_DATA_TYPE_BFLOAT16, 2, (void*)wqkv, gd, gs, bd, es, CU_TENSOR_MAP_INTERLEAVE_NONE, CU_TENSOR_MAP_SWIZZLE_128B, CU_TENSOR_MAP_L2_PROMOTION_L2_128B, CU_TENSOR_MAP_FLOAT_OOB_FILL_NONE);
  }
  {
    cuuint64_t gd[3] = {64, 640, 24}, gs[2] = {3072, 128};
    cuuint32_t bd[3] = {64, 64, 3};
    enc(&tmG, CU_TENSOR_MAP_DATA_TYPE_BFLOAT16, 3, (void*)wg, gd, gs, bd, es, CU_TENSOR_MAP_INTERLEAVE_NONE, CU_TENSOR_MAP_SWIZZLE_128B, CU_TENSOR_MAP_L2_PROMOTION_L2_128B, CU_TENSOR_MAP_FLOAT_OOB_FILL_NONE);
    enc(&tmU, CU_TENSOR_MAP_DATA_TYPE_BFLOAT16, 3, (void*)wu, gd, gs, bd, es, CU_TENSOR_MAP_INTERLEAVE_NONE, CU_TENSOR_MAP_SWIZZLE_128B, CU_TENSOR_MAP_L2_PROMOTION_L2_128B, CU_TENSOR_MAP_FLOAT_OOB_FILL_NONE);
  }
  cudaStream_t st = cudaStreamPerThread;
  k1_qkv<<<128, 384, K1_SMEM, st>>>(tmX, tmW, x, wqkv, wo, wg, wu, wd);
  cudaLaunchAttribute at[1];
  at[0].id = cudaLaunchAttributeProgrammaticStreamSerialization;
  at[0].val.programmaticStreamSerializationAllowed = 1;
  cudaLaunchConfig_t cfg = {};
  cfg.stream = st; cfg.attrs = at; cfg.numAttrs = 1;
  cfg.gridDim = dim3(128); cfg.blockDim = dim3(512); cfg.dynamicSmemBytes = K2_SMEM;
  cudaLaunchKernelEx(&cfg, k2_attn, 0u);
  cfg.blockDim = dim3(384); cfg.dynamicSmemBytes = K3_SMEM;
  cudaLaunchKernelEx(&cfg, k3_ffn, tmG, tmU, x, (__nv_bfloat16*)d_out);
}
```

```cpp
#include <cuda_runtime.h>
#include <cuda_bf16.h>
#include <cuda.h>
#include <stdint.h>

namespace {

constexpr int S_ = 2048, D_ = 640, F_ = 1536;
constexpr float LN_EPS = 1e-5f;
constexpr uint32_t POLY_MASK = 0xD5D5u;

__device__ __align__(1024) uint8_t g_qkv[16 * 288 * 2048];
__device__ __align__(1024) uint8_t g_o[16 * 80 * 2048];
__device__ __align__(1024) uint8_t g_h[16 * 80 * 2048];
__device__ __align__(1024) uint8_t g_H[16 * 192 * 2048];
__device__ __align__(1024) uint8_t g_wo[8 * 80 * 1280];
__device__ __align__(1024) uint8_t g_wd[8 * 192 * 1280];
__device__ uint4 g_st1[S_];
__device__ uint4 g_cs1[16 * 640];
__device__ __align__(16) float g_cs2[3072];
__device__ uint4 g_st2[S_ * 8];
__device__ unsigned g_flags[448 * 32];
constexpr int FL_DONE = 0, FL_PREP = 1, FL_PREP2 = 2, FL_IN = 3, FL_O = 4, FL_C = 36, FL_D = 68, FL_QKV = 192;

#define TLS(k, s)
#define WG_FENCE() asm volatile("wgmma.fence.sync.aligned;" ::: "memory")
#define WG_COMMIT() asm volatile("wgmma.commit_group.sync.aligned;" ::: "memory")
#define WG_WAIT(n) asm volatile("wgmma.wait_group.sync.aligned %0;" ::"n"(n) : "memory")
__device__ __forceinline__ uint64_t mkdesc(uint32_t addr, uint32_t lbo, uint32_t sbo, int swz) {
  return (uint64_t)((addr & 0x3FFFF) >> 4) | ((uint64_t)(lbo >> 4) << 16) | ((uint64_t)(sbo >> 4) << 32) | ((uint64_t)swz << 62);
}
__device__ __forceinline__ uint32_t smem_u32(const void* p) { return (uint32_t)__cvta_generic_to_shared(p); }
__device__ __forceinline__ void mbar_init(uint32_t bar, int cnt) { asm volatile("mbarrier.init.shared::cta.b64 [%0], %1;" ::"r"(bar), "r"(cnt) : "memory"); }
__device__ __forceinline__ void mbar_expect(uint32_t bar, uint32_t bytes) { asm volatile("mbarrier.arrive.expect_tx.shared::cta.b64 _, [%0], %1;" ::"r"(bar), "r"(bytes) : "memory"); }
__device__ __forceinline__ void mbar_arrive(uint32_t bar) { asm volatile("mbarrier.arrive.shared::cta.b64 _, [%0];" ::"r"(bar) : "memory"); }
__device__ __forceinline__ void mbar_wait(uint32_t bar, uint32_t par) {
  asm volatile("{\n.reg .pred p;\n.reg .u32 c;\nmov.u32 c, 0;\nLW:\nmbarrier.try_wait.parity.shared::cta.b64 p, [%0], %1;\n@p bra.uni LD;\n"
               "add.u32 c, c, 1;\nsetp.lt.u32 p, c, 2000000;\n@p bra.uni LW;\ntrap;\nLD:\n}" ::"r"(bar), "r"(par) : "memory");
}
__device__ __forceinline__ void bulk_g2s(uint32_t dst, const void* src, uint32_t bytes, uint32_t bar) {
  asm volatile("cp.async.bulk.shared::cluster.global.mbarrier::complete_tx::bytes [%0], [%1], %2, [%3];" ::"r"(dst), "l"(src), "r"(bytes), "r"(bar) : "memory");
}
__device__ __forceinline__ void tma2d(uint32_t dst, const CUtensorMap* tm, int c0, int c1, uint32_t bar) {
  asm volatile("cp.async.bulk.tensor.2d.shared::cluster.global.mbarrier::complete_tx::bytes [%0], [%1, {%3, %4}], [%2];" ::"r"(dst), "l"(tm), "r"(bar), "r"(c0), "r"(c1) : "memory");
}
__device__ __forceinline__ void tma3d(uint32_t dst, const CUtensorMap* tm, int c0, int c1, int c2, uint32_t bar) {
  asm volatile("cp.async.bulk.tensor.3d.shared::cluster.global.mbarrier::complete_tx::bytes [%0], [%1, {%3, %4, %5}], [%2];" ::"r"(dst), "l"(tm), "r"(bar), "r"(c0), "r"(c1), "r"(c2) : "memory");
}
__device__ __forceinline__ void tm_prefetch(const CUtensorMap* tm) { asm volatile("prefetch.tensormap [%0];" ::"l"(tm) : "memory"); }
#define FENCE_ASYNC_GLOBAL() asm volatile("fence.proxy.async.global;" ::: "memory")
__device__ __forceinline__ void tma2d_store(const CUtensorMap* tm, uint32_t src, int c0, int c1) {
  asm volatile("cp.async.bulk.tensor.2d.global.shared::cta.bulk_group [%0, {%2, %3}], [%1];" ::"l"(tm), "r"(src), "r"(c0), "r"(c1) : "memory");
}
__device__ __forceinline__ void bulk_s2g(void* dst, uint32_t src, uint32_t bytes) {
  asm volatile("cp.async.bulk.global.shared::cta.bulk_group [%0], [%1], %2;" ::"l"(dst), "r"(src), "r"(bytes) : "memory");
}
__device__ __forceinline__ void l2_prefetch(const void* p, uint32_t bytes) { asm volatile("cp.async.bulk.prefetch.L2.global [%0], %1;" ::"l"(p), "r"(bytes) : "memory"); }
#define BULK_COMMIT() asm volatile("cp.async.bulk.commit_group;" ::: "memory")
#define BULK_WAIT() asm volatile("cp.async.bulk.wait_group 0;" ::: "memory")
#define BULK_WAIT_READ() asm volatile("cp.async.bulk.wait_group.read 0;" ::: "memory")
#define FENCE_ASYNC_SMEM() asm volatile("fence.proxy.async.shared::cta;" ::: "memory")
__device__ __forceinline__ void stsm4(uint32_t addr, uint32_t r0, uint32_t r1, uint32_t r2, uint32_t r3) {
  asm volatile("stmatrix.sync.aligned.m8n8.x4.shared.b16 [%0], {%1, %2, %3, %4};" ::"r"(addr), "r"(r0), "r"(r1), "r"(r2), "r"(r3));
}
__device__ __forceinline__ void stsm2(uint32_t addr, uint32_t r0, uint32_t r1) {
  asm volatile("stmatrix.sync.aligned.m8n8.x2.shared.b16 [%0], {%1, %2};" ::"r"(addr), "r"(r0), "r"(r1));
}
__device__ __forceinline__ void ldsm4(uint32_t addr, uint32_t& r0, uint32_t& r1, uint32_t& r2, uint32_t& r3) {
  asm volatile("ldmatrix.sync.aligned.m8n8.x4.shared.b16 {%0, %1, %2, %3}, [%4];" : "=r"(r0), "=r"(r1), "=r"(r2), "=r"(r3) : "r"(addr) : "memory");
}
__device__ __forceinline__ bool elect_one() {
  uint32_t p;
  asm volatile("{\n.reg .pred e;\nelect.sync _|e, 0xffffffff;\nselp.u32 %0, 1, 0, e;\n}" : "=r"(p));
  return p;
}
__device__ __forceinline__ void bar_sync(int id, int n) { asm volatile("bar.sync %0, %1;" ::"r"(id), "r"(n) : "memory"); }
__device__ __forceinline__ void bar_arrive(int id, int n) { asm volatile("bar.arrive %0, %1;" ::"r"(id), "r"(n) : "memory"); }
__device__ __forceinline__ void flag_add(unsigned* f) { asm volatile("fence.acq_rel.gpu;\nred.relaxed.gpu.global.add.u32 [%0], 1;" ::"l"(f) : "memory"); }
__device__ __forceinline__ void flag_wait(const unsigned* f, unsigned n) {
  asm volatile("{\n.reg .pred p;\n.reg .u32 c, v;\nmov.u32 c, 0;\nFW:\nld.acquire.gpu.global.u32 v, [%0];\nsub.u32 v, v, %1;\nsetp.ge.s32 p, v, 0;\n@p bra.uni FD;\n"
               "add.u32 c, c, 1;\nsetp.lt.u32 p, c, 2000000;\n@p bra.uni FW;\ntrap;\nFD:\n}" ::"l"(f), "r"(n) : "memory");
}
__device__ __forceinline__ uint4 ldg128(const uint4* p) {
  uint4 v; asm volatile("ld.global.v4.u32 {%0, %1, %2, %3}, [%4];" : "=r"(v.x), "=r"(v.y), "=r"(v.z), "=r"(v.w) : "l"(p) : "memory"); return v;
}
__device__ __forceinline__ uint32_t ldg32(const uint32_t* p) {
  uint32_t v; asm volatile("ld.global.u32 %0, [%1];" : "=r"(v) : "l"(p) : "memory"); return v;
}
__device__ __forceinline__ void flag_wait_warp(const unsigned* f, unsigned n) {
  asm volatile("{\n.reg .pred p;\n.reg .u32 c, v;\nmov.u32 c, 0;\nFW:\nld.acquire.gpu.global.u32 v, [%0];\nsub.u32 v, v, %1;\nsetp.ge.s32 p, v, 0;\n"
               "vote.sync.all.pred p, p, 0xffffffff;\n@p bra.uni FD;\nadd.u32 c, c, 1;\nsetp.lt.u32 p, c, 2000000;\n@p bra.uni FW;\ntrap;\nFD:\n}" ::"l"(f), "r"(n) : "memory");
}
__device__ __forceinline__ void st_tag(uint4* p, float a, float b, float c, unsigned tag) {
  asm volatile("{\n.reg .b128 v;\n.reg .b64 l, h;\nmov.b64 l, {%1, %2};\nmov.b64 h, {%3, %4};\nmov.b128 v, {l, h};\nst.relaxed.gpu.global.b128 [%0], v;\n}"
               ::"l"(p), "r"(__float_as_uint(a)), "r"(__float_as_uint(b)), "r"(__float_as_uint(c)), "r"(tag) : "memory");
}
__device__ __forceinline__ uint4 ld_tag(const uint4* p) {
  uint4 r;
  asm volatile("{\n.reg .b128 v;\n.reg .b64 l, h;\nld.relaxed.gpu.global.b128 v, [%4];\nmov.b128 {l, h}, v;\nmov.b64 {%0, %1}, l;\nmov.b64 {%2, %3}, h;\n}"
               : "=r"(r.x), "=r"(r.y), "=r"(r.z), "=r"(r.w) : "l"(p) : "memory");
  return r;
}
__device__ __forceinline__ float ex2f(float x) { float y; asm("ex2.approx.ftz.f32 %0, %1;" : "=f"(y) : "f"(x)); return y; }
__device__ __forceinline__ float tanhf_(float x) { float y; asm("tanh.approx.f32 %0, %1;" : "=f"(y) : "f"(x)); return y; }
__device__ __forceinline__ uint32_t packbf(float lo, float hi) { uint32_t r; asm("cvt.rn.bf16x2.f32 %0, %1, %2;" : "=r"(r) : "f"(hi), "f"(lo)); return r; }
__device__ __forceinline__ float bflo(uint32_t v) { return __uint_as_float(v << 16); }
__device__ __forceinline__ float bfhi(uint32_t v) { return __uint_as_float(v & 0xFFFF0000u); }
template <int N> __device__ __forceinline__ void fence_f(float (&a)[N]) {
#pragma unroll
  for (int i = 0; i < N; i++) asm volatile("" : "+f"(a[i])::"memory");
}
template <int N> __device__ __forceinline__ void fence_u(uint32_t (&a)[N]) {
#pragma unroll
  for (int i = 0; i < N; i++) asm volatile("" : "+r"(a[i])::"memory");
}

template<int TB> __device__ __forceinline__ void wgmma_n128_ss(float (&d)[64], uint64_t da, uint64_t db, int scale_d) {
  asm volatile("{\n.reg .pred p;\nsetp.ne.b32 p, %66, 0;\n"
    "wgmma.mma_async.sync.aligned.m64n128k16.f32.bf16.bf16 "
    "{%0, %1, %2, %3, %4, %5, %6, %7, %8, %9, %10, %11, %12, %13, %14, %15, %16, %17, %18, %19, %20, %21, %22, %23, "
    "%24, %25, %26, %27, %28, %29, %30, %31, %32, %33, %34, %35, %36, %37, %38, %39, %40, %41, %42, %43, %44, %45, %46, %47, "
    "%48, %49, %50, %51, %52, %53, %54, %55, %56, %57, %58, %59, %60, %61, %62, %63}, "
    "%64, %65, p, 1, 1, 0, %67;\n}\n"
    : "+f"(d[0]), "+f"(d[1]), "+f"(d[2]), "+f"(d[3]), "+f"(d[4]), "+f"(d[5]), "+f"(d[6]), "+f"(d[7]), "+f"(d[8]), "+f"(d[9]), "+f"(d[10]), "+f"(d[11]),
      "+f"(d[12]), "+f"(d[13]), "+f"(d[14]), "+f"(d[15]), "+f"(d[16]), "+f"(d[17]), "+f"(d[18]), "+f"(d[19]), "+f"(d[20]), "+f"(d[21]), "+f"(d[22]), "+f"(d[23]),
      "+f"(d[24]), "+f"(d[25]), "+f"(d[26]), "+f"(d[27]), "+f"(d[28]), "+f"(d[29]), "+f"(d[30]), "+f"(d[31]), "+f"(d[32]), "+f"(d[33]), "+f"(d[34]), "+f"(d[35]),
      "+f"(d[36]), "+f"(d[37]), "+f"(d[38]), "+f"(d[39]), "+f"(d[40]), "+f"(d[41]), "+f"(d[42]), "+f"(d[43]), "+f"(d[44]), "+f"(d[45]), "+f"(d[46]), "+f"(d[47]),
      "+f"(d[48]), "+f"(d[49]), "+f"(d[50]), "+f"(d[51]), "+f"(d[52]), "+f"(d[53]), "+f"(d[54]), "+f"(d[55]), "+f"(d[56]), "+f"(d[57]), "+f"(d[58]), "+f"(d[59]),
      "+f"(d[60]), "+f"(d[61]), "+f"(d[62]), "+f"(d[63])
    : "l"(da), "l"(db), "r"(scale_d), "n"(TB));
}
template<int TB> __device__ __forceinline__ void wgmma_n192_ss(float (&d)[96], uint64_t da, uint64_t db, int scale_d) {
  asm volatile("{\n.reg .pred p;\nsetp.ne.b32 p, %98, 0;\n"
    "wgmma.mma_async.sync.aligned.m64n192k16.f32.bf16.bf16 "
    "{%0, %1, %2, %3, %4, %5, %6, %7, %8, %9, %10, %11, %12, %13, %14, %15, %16, %17, %18, %19, %20, %21, %22, %23, "
    "%24, %25, %26, %27, %28, %29, %30, %31, %32, %33, %34, %35, %36, %37, %38, %39, %40, %41, %42, %43, %44, %45, %46, %47, "
    "%48, %49, %50, %51, %52, %53, %54, %55, %56, %57, %58, %59, %60, %61, %62, %63, %64, %65, %66, %67, %68, %69, %70, %71, "
    "%72, %73, %74, %75, %76, %77, %78, %79, %80, %81, %82, %83, %84, %85, %86, %87, %88, %89, %90, %91, %92, %93, %94, %95}, "
    "%96, %97, p, 1, 1, 0, %99;\n}\n"
    : "+f"(d[0]), "+f"(d[1]), "+f"(d[2]), "+f"(d[3]), "+f"(d[4]), "+f"(d[5]), "+f"(d[6]), "+f"(d[7]), "+f"(d[8]), "+f"(d[9]), "+f"(d[10]), "+f"(d[11]),
      "+f"(d[12]), "+f"(d[13]), "+f"(d[14]), "+f"(d[15]), "+f"(d[16]), "+f"(d[17]), "+f"(d[18]), "+f"(d[19]), "+f"(d[20]), "+f"(d[21]), "+f"(d[22]), "+f"(d[23]),
      "+f"(d[24]), "+f"(d[25]), "+f"(d[26]), "+f"(d[27]), "+f"(d[28]), "+f"(d[29]), "+f"(d[30]), "+f"(d[31]), "+f"(d[32]), "+f"(d[33]), "+f"(d[34]), "+f"(d[35]),
      "+f"(d[36]), "+f"(d[37]), "+f"(d[38]), "+f"(d[39]), "+f"(d[40]), "+f"(d[41]), "+f"(d[42]), "+f"(d[43]), "+f"(d[44]), "+f"(d[45]), "+f"(d[46]), "+f"(d[47]),
      "+f"(d[48]), "+f"(d[49]), "+f"(d[50]), "+f"(d[51]), "+f"(d[52]), "+f"(d[53]), "+f"(d[54]), "+f"(d[55]), "+f"(d[56]), "+f"(d[57]), "+f"(d[58]), "+f"(d[59]),
      "+f"(d[60]), "+f"(d[61]), "+f"(d[62]), "+f"(d[63]), "+f"(d[64]), "+f"(d[65]), "+f"(d[66]), "+f"(d[67]), "+f"(d[68]), "+f"(d[69]), "+f"(d[70]), "+f"(d[71]),
      "+f"(d[72]), "+f"(d[73]), "+f"(d[74]), "+f"(d[75]), "+f"(d[76]), "+f"(d[77]), "+f"(d[78]), "+f"(d[79]), "+f"(d[80]), "+f"(d[81]), "+f"(d[82]), "+f"(d[83]),
      "+f"(d[84]), "+f"(d[85]), "+f"(d[86]), "+f"(d[87]), "+f"(d[88]), "+f"(d[89]), "+f"(d[90]), "+f"(d[91]), "+f"(d[92]), "+f"(d[93]), "+f"(d[94]), "+f"(d[95])
    : "l"(da), "l"(db), "r"(scale_d), "n"(TB));
}
template<int TB> __device__ __forceinline__ void wgmma_n80_ss(float (&d)[40], uint64_t da, uint64_t db, int scale_d) {
  asm volatile("{\n.reg .pred p;\nsetp.ne.b32 p, %42, 0;\n"
    "wgmma.mma_async.sync.aligned.m64n80k16.f32.bf16.bf16 "
    "{%0, %1, %2, %3, %4, %5, %6, %7, %8, %9, %10, %11, %12, %13, %14, %15, %16, %17, %18, %19, %20, %21, %22, %23, "
    "%24, %25, %26, %27, %28, %29, %30, %31, %32, %33, %34, %35, %36, %37, %38, %39}, "
    "%40, %41, p, 1, 1, 0, %43;\n}\n"
    : "+f"(d[0]), "+f"(d[1]), "+f"(d[2]), "+f"(d[3]), "+f"(d[4]), "+f"(d[5]), "+f"(d[6]), "+f"(d[7]), "+f"(d[8]), "+f"(d[9]), "+f"(d[10]), "+f"(d[11]),
      "+f"(d[12]), "+f"(d[13]), "+f"(d[14]), "+f"(d[15]), "+f"(d[16]), "+f"(d[17]), "+f"(d[18]), "+f"(d[19]), "+f"(d[20]), "+f"(d[21]), "+f"(d[22]), "+f"(d[23]),
      "+f"(d[24]), "+f"(d[25]), "+f"(d[26]), "+f"(d[27]), "+f"(d[28]), "+f"(d[29]), "+f"(d[30]), "+f"(d[31]), "+f"(d[32]), "+f"(d[33]), "+f"(d[34]), "+f"(d[35]),
      "+f"(d[36]), "+f"(d[37]), "+f"(d[38]), "+f"(d[39])
    : "l"(da), "l"(db), "r"(scale_d), "n"(TB));
}
template<int TB> __device__ __forceinline__ void wgmma_n128_rs(float (&d)[64], uint32_t a0, uint32_t a1, uint32_t a2, uint32_t a3, uint64_t db) {
  asm volatile("{\n.reg .pred p;\nsetp.ne.b32 p, 1, 0;\n"
    "wgmma.mma_async.sync.aligned.m64n128k16.f32.bf16.bf16 "
    "{%0, %1, %2, %3, %4, %5, %6, %7, %8, %9, %10, %11, %12, %13, %14, %15, %16, %17, %18, %19, %20, %21, %22, %23, "
    "%24, %25, %26, %27, %28, %29, %30, %31, %32, %33, %34, %35, %36, %37, %38, %39, %40, %41, %42, %43, %44, %45, %46, %47, "
    "%48, %49, %50, %51, %52, %53, %54, %55, %56, %57, %58, %59, %60, %61, %62, %63}, "
    "{%64, %65, %66, %67}, %68, p, 1, 1, %69;\n}\n"
    : "+f"(d[0]), "+f"(d[1]), "+f"(d[2]), "+f"(d[3]), "+f"(d[4]), "+f"(d[5]), "+f"(d[6]), "+f"(d[7]), "+f"(d[8]), "+f"(d[9]), "+f"(d[10]), "+f"(d[11]),
      "+f"(d[12]), "+f"(d[13]), "+f"(d[14]), "+f"(d[15]), "+f"(d[16]), "+f"(d[17]), "+f"(d[18]), "+f"(d[19]), "+f"(d[20]), "+f"(d[21]), "+f"(d[22]), "+f"(d[23]),
      "+f"(d[24]), "+f"(d[25]), "+f"(d[26]), "+f"(d[27]), "+f"(d[28]), "+f"(d[29]), "+f"(d[30]), "+f"(d[31]), "+f"(d[32]), "+f"(d[33]), "+f"(d[34]), "+f"(d[35]),
      "+f"(d[36]), "+f"(d[37]), "+f"(d[38]), "+f"(d[39]), "+f"(d[40]), "+f"(d[41]), "+f"(d[42]), "+f"(d[43]), "+f"(d[44]), "+f"(d[45]), "+f"(d[46]), "+f"(d[47]),
      "+f"(d[48]), "+f"(d[49]), "+f"(d[50]), "+f"(d[51]), "+f"(d[52]), "+f"(d[53]), "+f"(d[54]), "+f"(d[55]), "+f"(d[56]), "+f"(d[57]), "+f"(d[58]), "+f"(d[59]),
      "+f"(d[60]), "+f"(d[61]), "+f"(d[62]), "+f"(d[63])
    : "r"(a0), "r"(a1), "r"(a2), "r"(a3), "l"(db), "n"(TB));
}
template<int TB> __device__ __forceinline__ void wgmma_n128_rs_z(float (&d)[64], uint32_t a0, uint32_t a1, uint32_t a2, uint32_t a3, uint64_t db) {
  asm volatile("{\n.reg .pred p;\nsetp.ne.b32 p, 0, 0;\n"
    "wgmma.mma_async.sync.aligned.m64n128k16.f32.bf16.bf16 "
    "{%0, %1, %2, %3, %4, %5, %6, %7, %8, %9, %10, %11, %12, %13, %14, %15, %16, %17, %18, %19, %20, %21, %22, %23, "
    "%24, %25, %26, %27, %28, %29, %30, %31, %32, %33, %34, %35, %36, %37, %38, %39, %40, %41, %42, %43, %44, %45, %46, %47, "
    "%48, %49, %50, %51, %52, %53, %54, %55, %56, %57, %58, %59, %60, %61, %62, %63}, "
    "{%64, %65, %66, %67}, %68, p, 1, 1, %69;\n}\n"
    : "=f"(d[0]), "=f"(d[1]), "=f"(d[2]), "=f"(d[3]), "=f"(d[4]), "=f"(d[5]), "=f"(d[6]), "=f"(d[7]), "=f"(d[8]), "=f"(d[9]), "=f"(d[10]), "=f"(d[11]),
      "=f"(d[12]), "=f"(d[13]), "=f"(d[14]), "=f"(d[15]), "=f"(d[16]), "=f"(d[17]), "=f"(d[18]), "=f"(d[19]), "=f"(d[20]), "=f"(d[21]), "=f"(d[22]), "=f"(d[23]),
      "=f"(d[24]), "=f"(d[25]), "=f"(d[26]), "=f"(d[27]), "=f"(d[28]), "=f"(d[29]), "=f"(d[30]), "=f"(d[31]), "=f"(d[32]), "=f"(d[33]), "=f"(d[34]), "=f"(d[35]),
      "=f"(d[36]), "=f"(d[37]), "=f"(d[38]), "=f"(d[39]), "=f"(d[40]), "=f"(d[41]), "=f"(d[42]), "=f"(d[43]), "=f"(d[44]), "=f"(d[45]), "=f"(d[46]), "=f"(d[47]),
      "=f"(d[48]), "=f"(d[49]), "=f"(d[50]), "=f"(d[51]), "=f"(d[52]), "=f"(d[53]), "=f"(d[54]), "=f"(d[55]), "=f"(d[56]), "=f"(d[57]), "=f"(d[58]), "=f"(d[59]),
      "=f"(d[60]), "=f"(d[61]), "=f"(d[62]), "=f"(d[63])
    : "r"(a0), "r"(a1), "r"(a2), "r"(a3), "l"(db), "n"(TB));
}
template<int TB> __device__ __forceinline__ void wgmma_n64_rs(float (&d)[32], uint32_t a0, uint32_t a1, uint32_t a2, uint32_t a3, uint64_t db) {
  asm volatile("{\n.reg .pred p;\nsetp.ne.b32 p, 1, 0;\n"
    "wgmma.mma_async.sync.aligned.m64n64k16.f32.bf16.bf16 "
    "{%0, %1, %2, %3, %4, %5, %6, %7, %8, %9, %10, %11, %12, %13, %14, %15, %16, %17, %18, %19, %20, %21, %22, %23, "
    "%24, %25, %26, %27, %28, %29, %30, %31}, "
    "{%32, %33, %34, %35}, %36, p, 1, 1, %37;\n}\n"
    : "+f"(d[0]), "+f"(d[1]), "+f"(d[2]), "+f"(d[3]), "+f"(d[4]), "+f"(d[5]), "+f"(d[6]), "+f"(d[7]), "+f"(d[8]), "+f"(d[9]), "+f"(d[10]), "+f"(d[11]),
      "+f"(d[12]), "+f"(d[13]), "+f"(d[14]), "+f"(d[15]), "+f"(d[16]), "+f"(d[17]), "+f"(d[18]), "+f"(d[19]), "+f"(d[20]), "+f"(d[21]), "+f"(d[22]), "+f"(d[23]),
      "+f"(d[24]), "+f"(d[25]), "+f"(d[26]), "+f"(d[27]), "+f"(d[28]), "+f"(d[29]), "+f"(d[30]), "+f"(d[31])
    : "r"(a0), "r"(a1), "r"(a2), "r"(a3), "l"(db), "n"(TB));
}
template<int TB> __device__ __forceinline__ void wgmma_n64_rs_z(float (&d)[32], uint32_t a0, uint32_t a1, uint32_t a2, uint32_t a3, uint64_t db) {
  asm volatile("{\n.reg .pred p;\nsetp.ne.b32 p, 0, 0;\n"
    "wgmma.mma_async.sync.aligned.m64n64k16.f32.bf16.bf16 "
    "{%0, %1, %2, %3, %4, %5, %6, %7, %8, %9, %10, %11, %12, %13, %14, %15, %16, %17, %18, %19, %20, %21, %22, %23, "
    "%24, %25, %26, %27, %28, %29, %30, %31}, "
    "{%32, %33, %34, %35}, %36, p, 1, 1, %37;\n}\n"
    : "=f"(d[0]), "=f"(d[1]), "=f"(d[2]), "=f"(d[3]), "=f"(d[4]), "=f"(d[5]), "=f"(d[6]), "=f"(d[7]), "=f"(d[8]), "=f"(d[9]), "=f"(d[10]), "=f"(d[11]),
      "=f"(d[12]), "=f"(d[13]), "=f"(d[14]), "=f"(d[15]), "=f"(d[16]), "=f"(d[17]), "=f"(d[18]), "=f"(d[19]), "=f"(d[20]), "=f"(d[21]), "=f"(d[22]), "=f"(d[23]),
      "=f"(d[24]), "=f"(d[25]), "=f"(d[26]), "=f"(d[27]), "=f"(d[28]), "=f"(d[29]), "=f"(d[30]), "=f"(d[31])
    : "r"(a0), "r"(a1), "r"(a2), "r"(a3), "l"(db), "n"(TB));
}
template<int TB> __device__ __forceinline__ void wgmma_n24_rs(float (&d)[12], uint32_t a0, uint32_t a1, uint32_t a2, uint32_t a3, uint64_t db) {
  asm volatile("{\n.reg .pred p;\nsetp.ne.b32 p, 1, 0;\n"
    "wgmma.mma_async.sync.aligned.m64n24k16.f32.bf16.bf16 "
    "{%0, %1, %2, %3, %4, %5, %6, %7, %8, %9, %10, %11}, "
    "{%12, %13, %14, %15}, %16, p, 1, 1, %17;\n}\n"
    : "+f"(d[0]), "+f"(d[1]), "+f"(d[2]), "+f"(d[3]), "+f"(d[4]), "+f"(d[5]), "+f"(d[6]), "+f"(d[7]), "+f"(d[8]), "+f"(d[9]), "+f"(d[10]), "+f"(d[11])
    : "r"(a0), "r"(a1), "r"(a2), "r"(a3), "l"(db), "n"(TB));
}

constexpr int A_ST = 4, A_A = 32768, A_STAGE = 49152;
constexpr int KV_BLK = 24576, Q_OFF = 196608;
constexpr int C_AOFF = 102400;
constexpr int D_ST = 6, D_STAGE = 32768, D_B = 24576;
constexpr int E_ST = 7, E_STAGE = 16384 + 10240;
constexpr int H_OFF = 200704;
constexpr int M_OFF = 221184;
constexpr int SMEM_BYTES = M_OFF + 8192 + 3072;
constexpr int B_AFULL = 0, B_PACK = 32, B_KV = 40, B_Q = 104, B_WO = 120, B_EP = 128, B_CFULL = 136, B_CEMPTY = 216, B_DFB = 296, B_DFA = 344,
              B_EFB = 440, B_EFA = 496, B_PUB = 608, B_DSK = 632, B_TWO = 640, B_AEMPTY = 640, B_DEMPTY = 672, B_EEMPTY = 720, B_CDONE = 776, B_DDONE = 784,
              B_MISC = 792, B_ASIDE = 792, B_AIMG = 800, B_PIECE = 808, B_NORM = 840, B_BDONE = 848, B_SIDE = 856, B_OD = 864, B_HPUB = 896, B_OPUB = 904, B_DEAD = 912;
__device__ __forceinline__ uint32_t e_slot(int s) { return 12288 + (s < 5 ? s + 2 : s - 5) * E_STAGE; }

#define D_EARLY 5
#define FENCE_KB 1
#define SKEW 4
#define COLLECT_NS 300
#define HELP_AFTER 0
struct Params {
  CUtensorMap tmX, tmW, tmQ, tmWo, tmWd, tmG, tmU, tmO, tmR;
  const __nv_bfloat16 *x, *wqkv, *wg, *wu;
  uint32_t zero;
};

__device__ __forceinline__ uint32_t exp2_pair(float y0, float y1, uint32_t cm) {
  const uint32_t L = __byte_perm(__float_as_uint(y0), __float_as_uint(y1), 0x6521);
  uint32_t zh, E, r;
  asm("lop3.b32 %0, %1, %2, 0x3F003F00, 0xEA;" : "=r"(zh) : "r"(L), "r"(cm));
  asm("lop3.b32 %0, %1, %2, 0x00010001, 0xBA;" : "=r"(E) : "r"(L), "r"(cm));
  asm("fma.rn.bf16x2 %0, %1, %2, %3;" : "=r"(r) : "r"(L), "r"(zh), "r"(E));
  return r;
}
__device__ __forceinline__ void att_store(const float (&o)[12], int h, int grp, int row, int lane) {
  const int q = lane & 3, odd = h & 1, src = (lane & ~3) | (odd ? 0 : 2);
  const float l0 = __shfl_sync(0xffffffffu, odd ? o[0] : o[8], src), l1 = __shfl_sync(0xffffffffu, odd ? o[2] : o[10], src);
  const float i0 = __fdividef(1.f, l0), i1 = __fdividef(1.f, l1);
  uint8_t* p = g_o + (grp * 80 + (h >> 1) * 5 + odd * 2) * 1024 + row * 16 + q * 4;
  if (!odd || q >= 2) { *(uint32_t*)(p) = packbf(o[0] * i0, o[1] * i0); *(uint32_t*)(p + 128) = packbf(o[2] * i1, o[3] * i1); }
  *(uint32_t*)(p + 1024) = packbf(o[4] * i0, o[5] * i0); *(uint32_t*)(p + 1024 + 128) = packbf(o[6] * i1, o[7] * i1);
  if (odd || q < 2) { *(uint32_t*)(p + 2048) = packbf(o[8] * i0, o[9] * i0); *(uint32_t*)(p + 2048 + 128) = packbf(o[10] * i1, o[11] * i1); }
}
__device__ __forceinline__ void load_q(uint32_t (&q)[8], const uint8_t* sm, int pass, int tid, uint32_t zero) {
  const uint8_t* qp = sm + Q_OFF + pass * 12288 + (tid >> 8) * 6144 + (((tid >> 5) & 7) * 16 + ((tid & 31) >> 2)) * 16 + (tid & 3) * 4;
  q[0] = *(const uint32_t*)(qp); q[1] = *(const uint32_t*)(qp + 128);
  q[2] = *(const uint32_t*)(qp + 2048); q[3] = *(const uint32_t*)(qp + 2048 + 128);
  q[4] = *(const uint32_t*)(qp + 4096); q[5] = *(const uint32_t*)(qp + 4096 + 128);
  q[6] = q[0] & zero; q[7] = q[1] & zero;
}
__device__ __forceinline__ void load_qkv(uint32_t sbase, uint32_t bars, int cta, int m, int part, unsigned ep, bool gate) {
  const int lane = threadIdx.x & 31, h = cta >> 2;
  const int tb = (part < 4 ? part : cta & 3) * 4 + m;
  const int c0 = (part == 4 ? 0 : (lane & 4) ? 1280 : 640) + h * 20 + (lane & 1) * 19;
  flag_wait_warp(g_flags + (FL_QKV + (tb + (lane & 2)) * 16 + (c0 >> 7)) * 32, 2 * ep);
  if (gate) mbar_wait(bars + (part ? B_KV : B_AIMG), 0);
  if (elect_one()) {
    FENCE_ASYNC_GLOBAL();
    const uint8_t* src = g_qkv + tb * 589824 + h * 6144;
    if (part == 4) {
      mbar_expect(bars + B_Q + 8 * m, 12288);
      bulk_g2s(sbase + Q_OFF + m * 12288, src, 6144, bars + B_Q + 8 * m);
      bulk_g2s(sbase + Q_OFF + m * 12288 + 6144, src + 2 * 589824, 6144, bars + B_Q + 8 * m);
    } else {
      const uint32_t dst = sbase + (4 * m + part) * KV_BLK, fb = bars + B_KV + 8 * (4 * m + part);
      mbar_expect(fb, KV_BLK);
#pragma unroll
      for (int c = 0; c < 4; c++) bulk_g2s(dst + c * 6144, src + (c >> 1) * 2 * 589824 + (1 + (c & 1)) * 196608, 6144, fb);
    }
  }
}
__device__ __forceinline__ void load_wo(const CUtensorMap* tmR, uint32_t sbase, uint32_t bars, int cta, unsigned ep, uint32_t gate) {
  flag_wait_warp(g_flags + FL_PREP * 32, 32 * ep);
  mbar_wait(bars + gate, 0);
  if (elect_one()) {
    FENCE_ASYNC_GLOBAL();
    mbar_expect(bars + B_WO, 102400 + 20480);
    bulk_g2s(sbase, g_wo + (cta & 7) * 102400, 102400, bars + B_WO);
    const int tok = (cta >> 4) * 256 + ((cta >> 3) & 1) * 64;
    tma3d(sbase + H_OFF, tmR, 0, tok, (cta & 7) * 10, bars + B_WO);
    tma3d(sbase + H_OFF + 10240, tmR, 0, tok + 128, (cta & 7) * 10, bars + B_WO);
  }
}
__device__ __forceinline__ bool att_safe(uint32_t bars, volatile unsigned* s_max) {
  mbar_wait(bars + B_NORM, 0);
  return __all_sync(0xffffffffu, __uint_as_float(s_max[0]) * __uint_as_float(s_max[1]) <= 4096.f);
}

__device__ __forceinline__ bool attention(const CUtensorMap* tmR, uint8_t* sm, uint32_t sbase, uint32_t bars, uint32_t zero, unsigned ep, int cta, unsigned* pub) {
  const int tid = threadIdx.x, wid = __shfl_sync(0xffffffffu, tid >> 5, 0), lane = tid & 31, wg = wid >> 2;
  const int h = cta >> 2, quarter = cta & 3;
  volatile unsigned* s_max = (volatile unsigned*)(sm + M_OFF + 8000);
  const uint32_t cm = 0x007F007Fu | zero;
  const uint64_t dk0 = mkdesc(sbase, 2048, 128, 0), dv0 = mkdesc(sbase + 6144, 128, 2048, 0);
  const int grp = (quarter * 4 + wg) * 2, row = (wid & 3) * 16 + (lane >> 2);
  uint32_t q[8];
  float o[12];
  const unsigned chores = (wid == 10 ? 0x0001 : wg == 1 ? 0x0004 : wid == 0 ? 0x0200 : wid == 12 ? 0x2000 : wid == 8 ? 0x1000 : 0) | ((wid & 3) ? 0 : 0x4000);
#pragma unroll 1
  for (int pass = 0; pass < 2; pass++) {
    mbar_wait(bars + B_Q + 8 * pass, 0);
    load_q(q, sm, pass, tid, zero);
#pragma unroll
    for (int i = 0; i < 12; i++) o[i] = 0.f;
    fence_u(q); fence_f(o);
    uint64_t dk = dk0, dv = dv0;
#pragma unroll 1
    for (int j = pass * 8; j < pass * 8 + 8; j++) {
      if (j < 8) mbar_wait(bars + B_KV + 8 * j, 0);
      if (j == 0 && (tid & 127) == 0) TLS(3, wg);
#pragma unroll
      for (int u = 0; u < 2; u++) {
        float s[64]; uint32_t p[32];
        WG_FENCE();
        wgmma_n128_rs_z<0>(s, q[0], q[1], q[2], q[3], dk + u * 768);
        wgmma_n128_rs<0>(s, q[4], q[5], q[6], q[7], dk + u * 768 + 256);
        WG_COMMIT();
        WG_WAIT(0);
        fence_f(s);
#pragma unroll
        for (int g = 0; g < 16; g++) {
          if ((POLY_MASK >> g) & 1) {
            p[2 * g] = exp2_pair(s[4 * g], s[4 * g + 1], cm);
            p[2 * g + 1] = exp2_pair(s[4 * g + 2], s[4 * g + 3], cm);
          } else {
            p[2 * g] = packbf(ex2f(s[4 * g]), ex2f(s[4 * g + 1]));
            p[2 * g + 1] = packbf(ex2f(s[4 * g + 2]), ex2f(s[4 * g + 3]));
          }
        }
        fence_u(p);
        WG_FENCE();
#pragma unroll
        for (int c = 0; c < 8; c++) wgmma_n24_rs<1>(o, p[4 * c], p[4 * c + 1], p[4 * c + 2], p[4 * c + 3], dv + u * 768 + c * 16);
        WG_COMMIT();
        WG_WAIT(0);
      }
      dk += KV_BLK >> 4; dv += KV_BLK >> 4;
      if (j == 12 && (tid & 127) == 0) mbar_arrive(bars + B_DEAD);
      if ((chores >> j) & 1) {
        if (j == 0) {
          if (pub && elect_one()) asm volatile("fence.acq_rel.gpu;\nred.relaxed.gpu.global.add.u32 [%0], 2;" ::"l"(pub) : "memory");
        } else if (j == 2) {
#pragma unroll 1
          for (int i = wid == 7 ? 0 : 1; i < 2; i++) load_qkv(sbase, bars, cta, 1, i ? wid - 4 : 4, ep, false);
        } else if (att_safe(bars, s_max)) {
          if (j == 9) {
            if (lane < 4) asm volatile("fence.acq_rel.gpu;\nred.relaxed.gpu.global.add.u32 [%0], 4;" ::"l"(g_flags + (FL_O + (quarter * 4 + lane) * 2) * 32) : "memory");
          }
          else if (j == 13) load_wo(tmR, sbase, bars, cta, ep, B_DEAD);
          else if (j == 12) flag_wait_warp(g_flags + (FL_O + (cta >> 3) * 2) * 32, 128 * ep);
          else {
            int last = 0;
            if (lane == 0) last = atomicAdd((unsigned*)s_max + 2, 1) == 3;
            if (__shfl_sync(0xffffffffu, last, 0) && elect_one()) {
              FENCE_ASYNC_GLOBAL();
#pragma unroll 1
              for (int kb = 0; kb < 4; kb++) {
                mbar_expect(bars + B_CFULL + 8 * kb, 16384);
                bulk_g2s(sbase + C_AOFF + kb * 16384, g_o + ((cta >> 3) * 160 + kb * 16) * 1024, 16384, bars + B_CFULL + 8 * kb);
              }
            }
          }
        }
        __syncwarp();
      }
    }
    fence_f(o);
    if ((tid & 127) == 0) TLS(3, 4 + 4 * pass + wg);
    att_store(o, h, grp + pass, row, lane);
    if (pass == 0) {
      mbar_wait(bars + B_Q + 8, 0);
      float km = 0.f;
#pragma unroll
      for (int r = 0; r < 5; r++) {
        const uint8_t* p = r < 4 ? sm + wid * 12288 + (r * 32 + lane) * 16 : sm + Q_OFF + (wid >> 2) * 6144 + ((wid & 3) * 32 + lane) * 16;
        const uint4 a = *(const uint4*)(p + (h & 1) * 4096), b = *(const uint4*)(p + 2048);
        const uint2 c = *(const uint2*)(p + ((h & 1) ? 8 : 4096));
        const uint32_t w[10] = {a.x, a.y, a.z, a.w, b.x, b.y, b.z, b.w, c.x, c.y};
        uint32_t n2 = 0;
#pragma unroll
        for (int e = 0; e < 10; e++) asm("fma.rn.bf16x2 %0, %1, %1, %0;" : "+r"(n2) : "r"(w[e]));
        float n = bflo(n2) + bfhi(n2);
        if (r < 4) {
          if ((POLY_MASK >> ((r * 4 + (lane >> 3)) & 15)) & 1) n *= 0.25f;
          km = __uint_as_float(max(__float_as_uint(km), __float_as_uint(n)));
        } else {
          const unsigned a0 = __reduce_max_sync(0xffffffffu, __float_as_uint(n)), a1 = __reduce_max_sync(0xffffffffu, __float_as_uint(km));
          if (lane == 0) { atomicMax((unsigned*)s_max, a0); atomicMax((unsigned*)s_max + 1, a1); mbar_arrive(bars + B_NORM); }
        }
      }
    }
  }
  const bool safe = att_safe(bars, s_max);
  if (!safe) {
#pragma unroll 1
    for (int pass = 0; pass < 2; pass++) {
      load_q(q, sm, pass, tid, zero);
      if (h & 1) { if (!(lane & 2)) { q[0] = 0; q[1] = 0; } } else if (lane & 2) { q[4] = 0; q[5] = 0; }
      fence_u(q);
#pragma unroll
      for (int i = 0; i < 12; i++) o[i] = 0.f;
      float m0 = -INFINITY, m1 = -INFINITY;
#pragma unroll 1
      for (int j = 0; j < 32; j++) {
        float s[32]; uint32_t p[16];
        const int off = (j >> 1) * 768 + (j & 1) * 64;
        WG_FENCE();
        wgmma_n64_rs_z<0>(s, q[0], q[1], q[2], q[3], dk0 + off);
        wgmma_n64_rs<0>(s, q[4], q[5], q[6], q[7], dk0 + off + 256);
        WG_COMMIT();
        WG_WAIT(0);
        fence_f(s);
        float n0 = m0, n1 = m1;
#pragma unroll
        for (int g = 0; g < 8; g++) {
          const float sc = ((POLY_MASK >> ((j & 1) * 8 + g)) & 1) ? 0.5f : 1.f;
          s[4 * g] *= sc; s[4 * g + 1] *= sc; s[4 * g + 2] *= sc; s[4 * g + 3] *= sc;
          n0 = fmaxf(n0, fmaxf(s[4 * g], s[4 * g + 1])); n1 = fmaxf(n1, fmaxf(s[4 * g + 2], s[4 * g + 3]));
        }
        n0 = fmaxf(n0, __shfl_xor_sync(0xffffffffu, n0, 1)); n0 = fmaxf(n0, __shfl_xor_sync(0xffffffffu, n0, 2));
        n1 = fmaxf(n1, __shfl_xor_sync(0xffffffffu, n1, 1)); n1 = fmaxf(n1, __shfl_xor_sync(0xffffffffu, n1, 2));
        const float a0 = ex2f(m0 - n0), a1 = ex2f(m1 - n1);
        m0 = n0; m1 = n1;
#pragma unroll
        for (int i = 0; i < 3; i++) { o[4 * i] *= a0; o[4 * i + 1] *= a0; o[4 * i + 2] *= a1; o[4 * i + 3] *= a1; }
#pragma unroll
        for (int g = 0; g < 8; g++) {
          p[2 * g] = packbf(ex2f(s[4 * g] - m0), ex2f(s[4 * g + 1] - m0));
          p[2 * g + 1] = packbf(ex2f(s[4 * g + 2] - m1), ex2f(s[4 * g + 3] - m1));
        }
        fence_u(p); fence_f(o);
        WG_FENCE();
#pragma unroll
        for (int c = 0; c < 4; c++) wgmma_n24_rs<1>(o, p[4 * c], p[4 * c + 1], p[4 * c + 2], p[4 * c + 3], dv0 + off + c * 16);
        WG_COMMIT();
        WG_WAIT(0);
        fence_f(o);
      }
      att_store(o, h, grp + pass, row, lane);
    }
  }
  if ((wid & 3) == 0) {
    int last = 0;
    if (lane == 0) { last = atomicAdd((unsigned*)s_max + 3, 1) == 3; mbar_arrive(bars + B_BDONE); }
    if (safe && __shfl_sync(0xffffffffu, last, 0) && elect_one()) {
      mbar_expect(bars + B_CFULL + 32, 16384);
      bulk_g2s(sbase + C_AOFF + 65536, g_o + ((cta >> 3) * 160 + 64) * 1024, 16384, bars + B_CFULL + 32);
    }
  }
  if (FENCE_KB < 0 || wg != 0 || !safe) {
    __threadfence();
    __syncwarp();
    if (lane < 2 && (lane || !safe)) asm volatile("red.relaxed.gpu.global.add.u32 [%0], 1;" ::"l"(g_flags + (FL_O + grp + lane) * 32) : "memory");
  }
  if (tid == 385) TLS(1, 5);
  if (!safe && wid == 12) load_wo(tmR, sbase, bars, cta, ep, B_BDONE);
  __syncwarp();
  return safe;
}

__device__ __forceinline__ void prep(const Params& P, uint8_t* sm, uint32_t sbase, uint32_t bars, int pb) {
  const int tid = threadIdx.x, warp = tid >> 5, lane = tid & 31;
  if (tid == 0) TLS(1, 8);
  unsigned ep = 0;
  if (tid == 0) ep = (__ldcg(g_flags + FL_DONE * 32) >> 7) + 1;
  __nanosleep(3000);
  if (warp >= 8) {
    const uint32_t bar = bars + (warp - 8) * 16, boff = 16384 + (warp - 8) * 20480;
    if (lane == 0) { mbar_init(bar, 1); mbar_init(bar + 8, 1); asm volatile("fence.mbarrier_init.release.cluster;" ::: "memory"); }
    const int u0 = pb * 8 + warp - 8;
#pragma unroll 1
    for (int n = 0; u0 + 32 * (n - 1) < 272; n++) {
      const int u = u0 + 32 * n;
      __syncwarp();
      if (u < 272 && lane == 0) {
        const bool isd = u >= 80;
        const int v = isd ? u - 80 : u, j = isd ? v / 24 : v / 10, kb = v - j * (isd ? 24 : 10);
        mbar_expect(bar + 8 * (n & 1), 10240);
        tma2d(sbase + boff + (n & 1) * 10240, isd ? &P.tmWd : &P.tmWo, j * 80, kb * 64, bar + 8 * (n & 1));
      }
      if (n > 0) {
        const int m = n - 1, w = u - 32;
        mbar_wait(bar + 8 * (m & 1), (m >> 1) & 1);
        uint4* dst = (uint4*)(w >= 80 ? g_wd + (w - 80) * 10240 : g_wo + w * 10240);
        const uint8_t* src = sm + boff + (m & 1) * 10240;
#pragma unroll 4
        for (int i = lane; i < 640; i += 32) {
          const int g = i >> 3, kc = g / 10, nn = g - kc * 10;
          dst[i] = *(const uint4*)(src + (kc * 8 + (i & 7)) * 160 + nn * 16);
        }
        if (m == 2) { __syncwarp(); if (lane == 0) flag_add(g_flags + FL_PREP * 32); }
      }
    }
    if (tid == 256) TLS(1, 9);
  } else if (warp < 6) {
    float* part = (float*)sm;
    const int ch = tid % 96, rg = tid / 96;
    const __nv_bfloat16* src = (pb < 2 ? P.wg : P.wu) + (pb & 1) * 768 + ch * 8 + (size_t)rg * 320 * F_;
    float a[8];
#pragma unroll
    for (int e = 0; e < 8; e++) a[e] = 0.f;
#pragma unroll 1
    for (int r0 = 0; r0 < 320; r0 += 16) {
      uint4 wv[16];
#pragma unroll
      for (int r = 0; r < 16; r++) wv[r] = __ldg((const uint4*)(src + (size_t)(r0 + r) * F_));
#pragma unroll
      for (int r = 0; r < 16; r++) {
        a[0] += bflo(wv[r].x); a[1] += bfhi(wv[r].x); a[2] += bflo(wv[r].y); a[3] += bfhi(wv[r].y);
        a[4] += bflo(wv[r].z); a[5] += bfhi(wv[r].z); a[6] += bflo(wv[r].w); a[7] += bfhi(wv[r].w);
      }
    }
    *(float4*)(part + rg * 768 + ch * 8) = make_float4(a[0], a[1], a[2], a[3]);
    *(float4*)(part + rg * 768 + ch * 8 + 4) = make_float4(a[4], a[5], a[6], a[7]);
    bar_sync(1, 192);
    const float4 p0 = *(float4*)(part + tid * 4), p1 = *(float4*)(part + 768 + tid * 4);
    *(float4*)(g_cs2 + pb * 768 + tid * 4) = make_float4(p0.x + p1.x, p0.y + p1.y, p0.z + p1.z, p0.w + p1.w);
    if (tid == 0) TLS(1, 10);
  } else if (warp == 6 && lane < 30) {
    l2_prefetch((const uint8_t*)(pb < 2 ? P.wg : P.wu) + (pb & 1) * 983040 + lane * 32768, 32768);
  }
  __syncthreads();
  if (tid == 0) {
    flag_add(g_flags + FL_PREP2 * 32);
    flag_wait(g_flags + FL_IN * 32, 128 * ep);
  }
}

__device__ __forceinline__ void publish_h(uint32_t sbase, uint32_t bars, int bi, int bj, int w, int t) {
  bar_sync(3 + 3 * w + t, 160);
  if (elect_one()) {
    bulk_s2g(g_H + ((bi * 2 + w) * 192 + bj * 24 + t * 8) * 1024, sbase + e_slot(t) + w * 8192, 8192);
    BULK_COMMIT(); BULK_WAIT();
    mbar_arrive(bars + B_OD + 8 * t);
    flag_add(g_flags + (FL_D + (bi * 2 + w) * 3 + t) * 32);
  }
  __syncwarp();
}

__global__ void __launch_bounds__(512, 1) fused_block(const __grid_constant__ Params P) {
  extern __shared__ __align__(1024) uint8_t sm[];
  float* s_cs = (float*)(sm + M_OFF);
  float2* s_st = (float2*)(sm + M_OFF + 8192);
  float* s_part = (float*)(sm + M_OFF + 2560);
  volatile unsigned* s_ep = (volatile unsigned*)(sm + M_OFF + 8016);
  const uint32_t sbase = smem_u32(sm), bars = sbase + M_OFF + 7040, himg = sbase + H_OFF;
  const int tid = threadIdx.x, warp = __shfl_sync(0xffffffffu, tid >> 5, 0), lane = tid & 31;
  if (tid == 0) TLS(0, 15);
  int cta = blockIdx.x;
  uint32_t nsm;
  asm volatile("mov.u32 %0, %%nsmid;" : "=r"(nsm));
  if (nsm == 132) {
    uint32_t smid;
    asm volatile("mov.u32 %0, %%smid;" : "=r"(smid));
    const int t = smid >> 1, u = t - 32;
    const int r = t < 32 ? ((t & 7) ? ((t & 7) - 1) * 8 + (t >> 3) : 56 + (t >> 3)) : t < 60 ? (u % 7) * 8 + 4 + u / 7 : t < 62 ? t + 4 : t - 2;
    cta = r * 2 + (smid & 1);
  }
  if (cta >= 128) { prep(P, sm, sbase, bars, cta - 128); return; }
  const int bi = cta >> 3, bj = cta & 7;
  const int ti = (cta >> 5) * 2 + ((cta >> 3) & 1), tj = ((cta >> 4) & 1) * 8 + (cta & 7);
  const int own = (80 * bj + 16) >> 5;

  if (warp == 0 && elect_one()) {
    TLS(0, 0);
#pragma unroll
    for (int s = 0; s < A_ST; s++) { mbar_init(bars + B_AFULL + 8 * s, 1); mbar_init(bars + B_AEMPTY + 8 * s, 2); }
    asm volatile("fence.mbarrier_init.release.cluster;" ::: "memory");
#pragma unroll 1
    for (int kb = 0; kb < (tj < 15 ? A_ST : 0); kb++) {
      const uint32_t st = sbase + kb * A_STAGE, fb = bars + B_AFULL + 8 * kb;
      mbar_expect(fb, A_STAGE);
      tma3d(st + A_A, &P.tmW, 0, kb * 64, tj * 2, fb);
      tma2d(st, &P.tmX, kb * 64, ti * 256, fb);
    }
  }
  __syncwarp();
  if (warp >= 12) {
    asm volatile("setmaxnreg.dec.sync.aligned.u32 48;");
    unsigned ep;
    if (warp == 12) {
    } else if (warp == 13) {
      if (elect_one()) {
#pragma unroll 8
        for (int i = B_PACK; i < B_DFA + 8; i += 8) mbar_init(bars + i, 1);
        mbar_init(bars + B_ASIDE, 128); mbar_init(bars + B_AIMG, 3); mbar_init(bars + B_NORM, 16); mbar_init(bars + B_BDONE, 4); mbar_init(bars + B_SIDE, 32); mbar_init(bars + B_HPUB, 1); mbar_init(bars + B_OPUB, 4); mbar_init(bars + B_DEAD, 4);
        asm volatile("fence.mbarrier_init.release.cluster;" ::: "memory");
      }
      __syncwarp();
    } else if (warp == 14) {
      if (elect_one()) {
#pragma unroll 6
        for (int i = B_DFA + 8; i < B_TWO; i += 8) mbar_init(bars + i, 1);
#pragma unroll 5
        for (int i = B_DEMPTY; i < B_MISC; i += 8) mbar_init(bars + i, 2);
#pragma unroll
        for (int i = 0; i < 4; i++) { mbar_init(bars + B_PIECE + 8 * i, 4); mbar_init(bars + B_OD + 8 * i, 2); }
        *(uint4*)(sm + M_OFF + 8000) = make_uint4(0, 0, 0, 0);
        asm volatile("fence.mbarrier_init.release.cluster;" ::: "memory");
      }
      __syncwarp();
    } else ep = __ldcg(g_flags + FL_DONE * 32);
    __syncthreads();
    if (tid == 480) {
      *s_ep = (ep >> 7) + 1; mbar_arrive(bars + B_EP);
      asm volatile("red.relaxed.gpu.global.add.u32 [%0], 1;" ::"l"(g_flags + FL_IN * 32) : "memory");
      tm_prefetch(&P.tmQ); tm_prefetch(&P.tmG); tm_prefetch(&P.tmU); tm_prefetch(&P.tmO); tm_prefetch(&P.tmR);
    }
    if (warp == 12) {
      if (tj < 15) {
#pragma unroll 1
        for (int kb = A_ST; kb < 10; kb++) {
          const int s = kb & 3;
          mbar_wait(bars + B_AEMPTY + 8 * s, ((kb >> 2) - 1) & 1);
          if (elect_one()) {
            const uint32_t st = sbase + s * A_STAGE, fb = bars + B_AFULL + 8 * s;
            mbar_expect(fb, A_STAGE);
            tma3d(st + A_A, &P.tmW, 0, kb * 64, tj * 2, fb);
            tma2d(st, &P.tmX, kb * 64, ti * 256, fb);
          }
        }
      }
    }
    mbar_wait(bars + B_EP, 0);
    ep = *s_ep;
    if (tj < 15) mbar_wait(bars + B_PACK, 0);
#pragma unroll 1
    for (int i = warp == 15 ? 0 : 1; i < 2; i++) load_qkv(sbase, bars, cta, 0, i ? warp - 12 : 4, ep, i && (tj < 15 || warp > 12));
    if (tid == 384) TLS(1, 1);
    asm volatile("setmaxnreg.inc.sync.aligned.u32 128;");
  } else if (warp >= 8) {
    __syncthreads();
    {
      const int t = tid - 256, sw = warp - 8;
      mbar_wait(bars + B_EP, 0);
      const unsigned ep = *s_ep;
      if (tj < 15) mbar_wait(bars + B_AFULL + 8 * HELP_AFTER, 0);
      {
        uint4 wv[10], xv[10];
        const uint4* wp = (const uint4*)(P.wqkv + (size_t)(bi * 40 + sw * 10) * 1920 + bj * 240) + min(lane, 29);
        const uint4* xp = (const uint4*)(P.x + (size_t)(bi * 128 + bj * 16 + sw * 4 + (lane >> 3)) * D_) + (lane & 7);
#pragma unroll
        for (int r = 0; r < 10; r++) { xv[r] = ldg128(xp + r * 8); wv[r] = ldg128(wp + r * 240); }
        float s1 = 0.f, s2 = 0.f, s3 = 0.f, s4 = 0.f, a[8];
#pragma unroll
        for (int e = 0; e < 8; e++) a[e] = 0.f;
#pragma unroll
        for (int r = 0; r < 10; r++) {
          const uint32_t xw[4] = {xv[r].x, xv[r].y, xv[r].z, xv[r].w};
#pragma unroll
          for (int e = 0; e < 4; e++) {
            const float d0 = bflo(xw[e]), d1 = bfhi(xw[e]);
            s1 += d0; s3 += d1; s2 = fmaf(d0, d0, s2); s4 = fmaf(d1, d1, s4);
          }
          a[0] += bflo(wv[r].x); a[1] += bfhi(wv[r].x); a[2] += bflo(wv[r].y); a[3] += bfhi(wv[r].y);
          a[4] += bflo(wv[r].z); a[5] += bfhi(wv[r].z); a[6] += bflo(wv[r].w); a[7] += bfhi(wv[r].w);
        }
        if (lane < 30) {
          *(float4*)(s_part + sw * 240 + lane * 8) = make_float4(a[0], a[1], a[2], a[3]);
          *(float4*)(s_part + sw * 240 + lane * 8 + 4) = make_float4(a[4], a[5], a[6], a[7]);
        }
        s1 += s3; s2 += s4;
#pragma unroll
        for (int o = 4; o; o >>= 1) { s1 += __shfl_xor_sync(0xffffffffu, s1, o); s2 += __shfl_xor_sync(0xffffffffu, s2, o); }
        s1 *= (1.f / D_);
        if ((lane & 7) == 0) st_tag(g_st1 + bi * 128 + bj * 16 + sw * 4 + (lane >> 3), s1, rsqrtf(fmaxf(s2 * (1.f / D_) - s1 * s1, 0.f) + LN_EPS), 0.f, ep);
      }
      bar_sync(2, 128);
      if (t == 0) TLS(0, 7);
      if (t < 80) {
        const float* p = s_part + t * 3;
        st_tag(g_cs1 + bi * 640 + bj * 80 + t, (p[0] + p[240]) + (p[480] + p[720]), (p[1] + p[241]) + (p[481] + p[721]), (p[2] + p[242]) + (p[482] + p[722]), ep);
      }
      if (tj < 15) {
        const int w0 = tj * 128 / 3, dl = tj * 128 - 3 * w0;
        uint4 sv, sw2, v[16];
        const uint4* cp = g_cs1 + min(w0 + t, 639);
#pragma unroll 1
        for (int it = 0;; it++) {
          __nanosleep(COLLECT_NS);
          sv = ld_tag(g_st1 + ti * 256 + t); sw2 = ld_tag(g_st1 + ti * 256 + 128 + t);
          unsigned bad = (sv.w ^ ep) | (sw2.w ^ ep);
          if (t < 44) {
#pragma unroll
            for (int r = 0; r < 16; r++) v[r] = ld_tag(cp + r * 640);
#pragma unroll
            for (int r = 0; r < 16; r++) bad |= v[r].w ^ ep;
          }
          if (!__any_sync(0xffffffffu, bad)) break;
          if (it > 1000000) __trap();
        }
        s_st[t] = make_float2(__uint_as_float(sv.x), __uint_as_float(sv.y));
        s_st[t + 128] = make_float2(__uint_as_float(sw2.x), __uint_as_float(sw2.y));
        if (t < 44) {
          float c0 = 0.f, c1 = 0.f, c2 = 0.f;
#pragma unroll
          for (int r = 0; r < 16; r++) { c0 += __uint_as_float(v[r].x); c1 += __uint_as_float(v[r].y); c2 += __uint_as_float(v[r].z); }
          float* p = s_cs + 2 + t * 3 - dl;
          p[0] = c0; p[1] = c1; p[2] = c2;
        }
      }
      mbar_arrive(bars + B_ASIDE);
      if (t == 0) TLS(0, 6);
      if (tj < 15 && sw < 3) {
        const int r0 = tj % 5, p0 = (tj * 16 / 5) * 6 + r0 + (r0 > 2), o = 9 + (r0 == 2);
#pragma unroll 1
        for (int pc = sw; pc < (sw == 2 ? 4 : sw + 1); pc++) {
          mbar_wait(bars + B_PIECE + 8 * pc, 0);
          if (elect_one()) {
#pragma unroll 1
            for (int w = 0; w < 4; w++) {
              const uint32_t img = sbase + w * A_STAGE + pc * 8192;
              const int c0 = ((pc & 1) * 4 + w) * 32, c1 = (ti * 2 + (pc >> 1)) * 288 + p0;
              tma2d_store(&P.tmQ, img, c0, c1);
              tma2d_store(&P.tmQ, img + o * 256, c0, c1 + o);
            }
            BULK_COMMIT();
          }
        }
        if (elect_one()) {
          BULK_WAIT();
          mbar_arrive(bars + B_AIMG);
          if (sw == 2) TLS(0, 9);
          if (sw < 2) flag_add(g_flags + (FL_QKV + ti * 32 + tj) * 32);
          if (sw == 1) TLS(0, 4);
        }
      }
      __syncwarp();
    }
  } else {
    asm volatile("setmaxnreg.inc.sync.aligned.u32 168;");
    const int wg = warp >> 2, q = lane & 3;
    __syncthreads();
    if (tj < 15) {
      float ac[2][64];
      const uint64_t da0 = mkdesc(sbase + wg * 8192, 16, 1024, 1), db0 = mkdesc(sbase + A_A, 8192, 1024, 1);
#pragma unroll 1
      for (int kb = 0; kb < 10 - SKEW; kb++) {
        const int s = kb & 3;
        mbar_wait(bars + B_AFULL + 8 * s, (kb >> 2) & 1);
        if (kb == 0 && tid == 0) TLS(0, 1);
        const uint64_t da = da0 + s * (A_STAGE >> 4), db = db0 + s * (A_STAGE >> 4);
        WG_FENCE();
#pragma unroll
        for (int k = 0; k < 4; k++) {
          wgmma_n128_ss<1>(ac[0], da + k * 2, db + k * 128, (kb | k) != 0);
          wgmma_n128_ss<1>(ac[1], da + k * 2 + 1024, db + k * 128, (kb | k) != 0);
        }
        WG_COMMIT();
        WG_WAIT(1);
        if (kb > 0 && (tid & 127) == 0) mbar_arrive(bars + B_AEMPTY + 8 * ((kb - 1) & 3));
      }
      if (wg == 1) {
        if (SKEW == 4) {
          WG_WAIT(0);
          if (tid == 128) mbar_arrive(bars + B_AEMPTY + 8);
        }
        mbar_wait(bars + B_PACK, 0);
      }
      const int ty = tj / 5, r0 = tj - ty * 5;
      const uint32_t pad = ty == 0 ? ((q & 1) ? 0x00003F80u : 0x3F803F80u) : ty == 1 ? ((q & 1) ? 0x0000BB73u : 0xC04B4440u) : ((q & 1) ? 0u : 0x00003F80u);
#pragma unroll
      for (int m = 0; m < 2; m++) {
#pragma unroll 1
        for (int kb = 10 - SKEW; kb < 10; kb++) {
          const int s = kb & 3;
          if (m == 0) mbar_wait(bars + B_AFULL + 8 * s, (kb >> 2) & 1);
          const uint64_t da = da0 + s * (A_STAGE >> 4) + m * 1024, db = db0 + s * (A_STAGE >> 4);
          WG_FENCE();
#pragma unroll
          for (int k = 0; k < 4; k++) wgmma_n128_ss<1>(ac[m], da + k * 2, db + k * 128, 1);
          WG_COMMIT();
          if (m == 0) {
            WG_WAIT(1);
            if (tid == 0) {
              if (kb == 6) mbar_arrive(bars + B_AEMPTY + 8);
              if (kb == 9) mbar_arrive(bars + B_PACK);
            }
          }
        }
        WG_WAIT(0);
        fence_f(ac[0]); fence_f(ac[1]);
        bar_sync(7 + wg, 128);
        if (m == 0) {
          if (tid == 0) TLS(0, 2);
          mbar_wait(bars + B_ASIDE, 0);
          if (tid == 0) TLS(0, 3);
        } else if (tid == 128) TLS(0, 5);
        const int rw = warp * 16;
        const float2 st0 = s_st[m * 128 + rw + (lane >> 2)], st1 = s_st[m * 128 + rw + (lane >> 2) + 8];
        const bool mu0 = ty == 1 && !((POLY_MASK >> (rw >> 3)) & 1), mu1 = ty == 1 && !((POLY_MASK >> ((rw >> 3) + 1)) & 1);
        const float sc = ty == 0 ? 0.32259642f : ty == 1 ? 2.f : 1.f;
        const float c0 = mu0 ? st0.y : st0.y * sc, c1 = mu1 ? st1.y : st1.y * sc;
        const uint32_t pd0 = mu0 ? 0u : pad, pd1 = mu1 ? 0u : pad;
        uint32_t v[32];
#pragma unroll
        for (int g = 0; g < 16; g++) {
          const float2 cs = *(const float2*)(s_cs + 2 + g * 8 + q * 2);
          const float* a = ac[m] + 4 * g;
          v[2 * g] = packbf((a[0] - st0.x * cs.x) * c0, (a[1] - st0.x * cs.y) * c0);
          v[2 * g + 1] = packbf((a[2] - st1.x * cs.x) * c1, (a[3] - st1.x * cs.y) * c1);
        }
        fence_u(v);
        const uint32_t img = sbase + (warp & 3) * A_STAGE + m * 16384 + wg * 8192;
        uint32_t ia = img + lane * 16;
#pragma unroll
        for (int g = 0; g < 16; g++) {
          if ((r0 + g) % 5 == 2) { stsm4(ia, q < 2 ? v[2 * g] : pd0, q < 2 ? v[2 * g + 1] : pd1, q < 2 ? pd0 : v[2 * g], q < 2 ? pd1 : v[2 * g + 1]); ia += 512; }
          else { stsm2(ia, v[2 * g], v[2 * g + 1]); ia += 256; }
        }
        FENCE_ASYNC_SMEM();
        __syncwarp();
        if (lane == 0) mbar_arrive(bars + B_PIECE + 8 * (m * 2 + wg));
      }
      if (tid == 128) TLS(0, 8);
    }
    asm volatile("setmaxnreg.dec.sync.aligned.u32 128;");
  }
  mbar_wait(bars + B_EP, 0);
  const unsigned ep = *s_ep;
  const bool safe = attention(&P.tmR, sm, sbase, bars, P.zero, ep, cta, tj < 15 ? g_flags + (FL_QKV + ti * 32 + 16 + tj) * 32 : nullptr);
  if (warp >= 12) {
    asm volatile("setmaxnreg.dec.sync.aligned.u32 24;");
    if (warp < 14) {
      const int w = warp - 12;
      bar_sync(1 + w, 160);
      if (elect_one()) {
        bulk_s2g(g_h + ((bi * 2 + w) * 80 + bj * 10) * 1024, himg + w * 10240, 10240);
        BULK_COMMIT(); BULK_WAIT();
        flag_add(g_flags + (FL_C + bi * 2 + w) * 32);
        if (w == 1) { mbar_arrive(bars + B_HPUB); TLS(2, 4); }
      }
      __syncwarp();
    }
#pragma unroll 1
    for (int t = warp > 12 ? warp - 13 : 0; t < 3; t += warp > 12 ? 3 : 2) publish_h(sbase, bars, bi, bj, warp > 12, t);
  } else if (warp >= 8) {
    asm volatile("setmaxnreg.dec.sync.aligned.u32 40;");
    if (warp == 8) {
      if (elect_one()) {
        int s = 0, ph = 1;
#pragma unroll 1
        for (int b = 0; b < 20; b++) {
          const int kb = b < 2 ? own + b : b - 2 + (b - 2 >= own ? 2 : 0);
          if (b < 2) { mbar_wait(bars + B_CEMPTY + 8 + 8 * b, 0); mbar_wait(bars + B_CEMPTY + 48 + 8 * b, 0); }
          else if (b == 2) mbar_wait(bars + B_CDONE, 0);
          else if (b == D_EARLY) mbar_wait(bars + B_HPUB, 0);
          else if (b >= D_ST) mbar_wait(bars + B_DEMPTY + 8 * s, ph);
          mbar_expect(bars + B_DFB + 8 * s, D_B);
          tma3d(sbase + s * D_STAGE, &P.tmG, 0, kb * 32, bj * 3, bars + B_DFB + 8 * s);
          tma3d(sbase + s * D_STAGE + 12288, &P.tmU, 0, kb * 32, bj * 3, bars + B_DFB + 8 * s);
          if (++s == D_ST) { s = 0; ph ^= 1; }
        }
        flag_wait(g_flags + FL_PREP2 * 32, 4 * ep);
        FENCE_ASYNC_GLOBAL();
        mbar_wait(bars + B_DEMPTY + 16, 0); mbar_wait(bars + B_DEMPTY + 24, 0);
        const uint8_t* wsrc = g_wd + bj * 192 * 1280;
        int t = -1, d = 4;
        s = 0; ph = 1;
#pragma unroll 1
        for (int u = 0; u < 24; u++) {
          const int kb = u < 3 ? 3 * bj + u : 3 * (d + (d >= bj)) + t;
          if (u == 2) mbar_wait(bars + B_DDONE, 0);
          if (u >= E_ST) mbar_wait(bars + B_EEMPTY + 8 * s, ph);
          mbar_expect(bars + B_EFB + 8 * s, 10240);
          bulk_g2s(sbase + e_slot(s) + 16384, wsrc + kb * 10240, 10240, bars + B_EFB + 8 * s);
          if (++s == E_ST) { s = 0; ph ^= 1; }
          if (++d == 7) { d = 0; t++; }
        }
        asm volatile("red.relaxed.gpu.global.add.u32 [%0], 1;" ::"l"(g_flags + FL_DONE * 32) : "memory");
      }
    } else if (warp < 11) {
      if (elect_one()) {
        const int w = warp - 9, grp = bi * 2 + w;
        if (w || !safe) flag_wait(g_flags + (FL_O + grp) * 32, 128 * ep);
        mbar_wait(bars + B_BDONE, 0);
        FENCE_ASYNC_GLOBAL();
        TLS(w ? 2 : 3, w ? 1 : 12);
#pragma unroll 1
        for (int kb = w || !safe ? 0 : 5; kb < 5; kb++) {
          const uint32_t fb = bars + B_CFULL + 40 * w + 8 * kb;
          if (w && kb) mbar_wait(bars + B_CEMPTY + 8 * (kb - 1), 0);
          mbar_expect(fb, 16384);
          bulk_g2s(sbase + C_AOFF + (w ? (kb ? kb - 1 : 5) : kb) * 16384, g_o + (grp * 80 + kb * 16) * 1024, 16384, fb);
        }
        flag_wait(g_flags + (FL_C + grp) * 32, 8 * ep);
        mbar_wait(bars + B_CDONE, 0);
        FENCE_ASYNC_GLOBAL();
        if (w == 1) TLS(2, 5);
        {
          int s = 2, ph = 1;
#pragma unroll 1
          for (int b = 2; b < 20; b++) {
            const uint32_t fb = bars + B_DFA + 48 * w + 8 * s;
            if (b >= D_ST) mbar_wait(bars + B_DEMPTY + 8 * s, ph);
            mbar_expect(fb, 4096);
            bulk_g2s(sbase + s * D_STAGE + D_B + w * 4096, g_h + (grp * 80 + (b - 2 + (b - 2 >= own ? 2 : 0)) * 4) * 1024, 4096, fb);
            if (++s == D_ST) { s = 0; ph ^= 1; }
          }
        }
        {
          int s = 3, ph = 1;
#pragma unroll 1
          for (int t = 0; t < 3; t++) {
            flag_wait(g_flags + (FL_D + grp * 3 + t) * 32, 8 * ep);
            if (t == 0) mbar_wait(bars + B_DDONE, 0);
            FENCE_ASYNC_GLOBAL();
            if (t == 0 && w == 1) TLS(2, 9);
#pragma unroll 1
            for (int d = 0; d < 7; d++) {
              const uint32_t fb = bars + B_EFA + 56 * w + 8 * s;
              if (t > 0 || d >= 4) {
                if (t == 0) mbar_wait(bars + B_OD + 8 * s, 0);
                mbar_wait(bars + B_EEMPTY + 8 * s, ph);
              }
              mbar_expect(fb, 8192);
              bulk_g2s(sbase + e_slot(s) + w * 8192, g_H + (grp * 192 + (3 * (d + (d >= bj)) + t) * 8) * 1024, 8192, fb);
              if (++s == E_ST) { s = 0; ph ^= 1; }
            }
          }
        }
      }
    } else {
      flag_wait_warp(g_flags + FL_PREP2 * 32, 4 * ep);
#pragma unroll 1
      for (int c = lane; c < 96; c += 32) *(float4*)(s_cs + c * 4) = __ldcg((const float4*)(g_cs2 + (c < 48 ? 0 : F_ - 192) + bj * 192 + c * 4));
      mbar_wait(bars + B_DFA + 48 + 16, 0);
#pragma unroll 1
      for (int r = lane; r < 128; r += 32) {
        float m0, s1, s2, m2;
        const uint4* p = g_st2 + bi * 1024 + r;
#pragma unroll 1
        for (int it = 0;; it++) {
          unsigned bad = 0;
          s1 = 0.f; s2 = 0.f; m2 = 0.f;
#pragma unroll 1
          for (int c0 = 0; c0 < 8; c0 += 4) {
            uint4 v[4];
#pragma unroll
            for (int c = 0; c < 4; c++) v[c] = ld_tag(p + (c0 + c) * 128);
            if (c0 == 0) m0 = __uint_as_float(v[0].x);
#pragma unroll
            for (int c = 0; c < 4; c++) {
              const float d = __uint_as_float(v[c].x) - m0;
              s1 += d; s2 = fmaf(d, d, s2); m2 += __uint_as_float(v[c].y); bad |= v[c].w ^ ep;
            }
          }
          if (!__any_sync(0xffffffffu, bad)) break;
          if (it > 1000000) __trap();
        }
        s1 *= 0.125f;
        s_st[r] = make_float2(m0 + s1, rsqrtf((m2 + 80.f * fmaxf(s2 - 8.f * s1 * s1, 0.f)) * (1.f / D_) + LN_EPS));
      }
      mbar_arrive(bars + B_SIDE);
      publish_h(sbase, bars, bi, bj, 0, 1);
    }
  } else {
    const int wg = warp >> 2, q = lane & 3;
    const int rl = warp * 16 + (lane >> 2);
    const int tok = ((bi >> 1) * 2 + wg) * 128 + (bi & 1) * 64 + (warp & 3) * 16;
    const uint32_t mrow = (lane >> 4) * 1024 + ((warp & 3) * 16 + (lane & 15)) * 16;
    const uint32_t hw = himg + wg * 10240;
    {
      uint32_t xr[20];
      float acc[40];
      const uint64_t da0 = mkdesc(sbase + C_AOFF, 1024, 128, 0), db0 = mkdesc(sbase, 1280, 128, 0);
      mbar_wait(bars + B_WO, 0);
#pragma unroll
      for (int g = 0; g < 5; g++) ldsm4(hw + mrow + g * 2048, xr[4 * g], xr[4 * g + 1], xr[4 * g + 2], xr[4 * g + 3]);
#pragma unroll 1
      for (int kb = 0; kb < 5; kb++) {
        mbar_wait(bars + B_CFULL + 40 * wg + 8 * kb, 0);
        if (kb == 0 && (tid & 127) == 0) TLS(2, 2 + 12 * wg);
        const uint64_t da = da0 + (wg ? (kb ? kb - 1 : 5) : kb) * 1024, db = db0 + kb * 1280;
        WG_FENCE();
#pragma unroll
        for (int k = 0; k < 8; k++) wgmma_n80_ss<1>(acc, da + k * 128, db + k * 160, (kb | k) != 0);
        WG_COMMIT();
        if (FENCE_KB >= 0 && wg == 0 && kb == FENCE_KB && safe) {
          __threadfence();
          __syncwarp();
          if (lane == 0) asm volatile("red.relaxed.gpu.global.add.u32 [%0], 1;" ::"l"(g_flags + (FL_O + (cta & 3) * 8 + 1) * 32) : "memory");
        }
        WG_WAIT(1);
        if (kb > 0 && (tid & 127) == 0) mbar_arrive(bars + B_CEMPTY + 40 * wg + 8 * (kb - 1));
      }
      WG_WAIT(0);
      fence_f(acc);
      if ((tid & 127) == 0) { mbar_arrive(bars + B_CDONE); TLS(2, 3 + 12 * wg); }
      float s0 = 0.f, s1 = 0.f;
#pragma unroll
      for (int g = 0; g < 10; g++) {
        xr[2 * g] = packbf(acc[4 * g] + bflo(xr[2 * g]), acc[4 * g + 1] + bfhi(xr[2 * g]));
        xr[2 * g + 1] = packbf(acc[4 * g + 2] + bflo(xr[2 * g + 1]), acc[4 * g + 3] + bfhi(xr[2 * g + 1]));
        if (g & 1) stsm4(hw + mrow + (g - 1) * 1024, xr[2 * g - 2], xr[2 * g - 1], xr[2 * g], xr[2 * g + 1]);
      }
      FENCE_ASYNC_SMEM();
      bar_sync(1 + wg, 160);
#pragma unroll
      for (int g = 0; g < 10; g++) {
        acc[4 * g] = bflo(xr[2 * g]); acc[4 * g + 1] = bfhi(xr[2 * g]); acc[4 * g + 2] = bflo(xr[2 * g + 1]); acc[4 * g + 3] = bfhi(xr[2 * g + 1]);
        s0 += acc[4 * g] + acc[4 * g + 1]; s1 += acc[4 * g + 2] + acc[4 * g + 3];
      }
      s0 += __shfl_xor_sync(0xffffffffu, s0, 1); s1 += __shfl_xor_sync(0xffffffffu, s1, 1);
      s0 += __shfl_xor_sync(0xffffffffu, s0, 2); s1 += __shfl_xor_sync(0xffffffffu, s1, 2);
      s0 *= (1.f / 80.f); s1 *= (1.f / 80.f);
      float q0 = 0.f, q1 = 0.f;
#pragma unroll
      for (int g = 0; g < 10; g++) {
        float d;
        d = acc[4 * g] - s0; q0 += d * d; d = acc[4 * g + 1] - s0; q0 += d * d;
        d = acc[4 * g + 2] - s1; q1 += d * d; d = acc[4 * g + 3] - s1; q1 += d * d;
      }
      q0 += __shfl_xor_sync(0xffffffffu, q0, 1); q1 += __shfl_xor_sync(0xffffffffu, q1, 1);
      q0 += __shfl_xor_sync(0xffffffffu, q0, 2); q1 += __shfl_xor_sync(0xffffffffu, q1, 2);
      if (q < 2) st_tag(g_st2 + (bi * 8 + bj) * 128 + rl + q * 8, q ? s1 : s0, q ? q1 : q0, 0.f, ep);
    }
    asm volatile("setmaxnreg.inc.sync.aligned.u32 224;");
    {
      float ag[96], au[96];
      const uint64_t da0 = mkdesc(sbase + D_B + wg * 4096, 1024, 128, 0), db0 = mkdesc(sbase, 4096, 1024, 1);
      const uint64_t dah = mkdesc(hw + (bj & 1) * 2048, 1024, 128, 0);
      int s = 0, ph = 0, pa = 1;
#pragma unroll 1
      for (int b = 0; b < 20; b++) {
        if (b == 16 && wg == 1) {
          WG_WAIT(0);
          if (tid == 128) mbar_arrive(bars + B_DEMPTY + 24);
          mbar_wait(bars + B_DSK, 0);
        }
        mbar_wait(bars + B_DFB + 8 * s, ph);
        if (b >= 2) mbar_wait(bars + B_DFA + 48 * wg + 8 * s, pa);
        if (b == 2 && (tid & 127) == 0) TLS(2, wg ? 13 : 6);
        const uint64_t da = b < 2 ? dah + b * 256 : da0 + s * (D_STAGE >> 4), db = db0 + s * (D_STAGE >> 4);
        WG_FENCE();
#pragma unroll
        for (int k = 0; k < 2; k++) {
          wgmma_n192_ss<1>(ag, da + k * 128, db + k * 128, (b | k) != 0);
          wgmma_n192_ss<1>(au, da + k * 128, db + k * 128 + (12288 >> 4), (b | k) != 0);
        }
        WG_COMMIT();
        WG_WAIT(1);
        if (b > 0 && (tid & 127) == 0 && (b != 16 || wg == 0)) mbar_arrive(bars + B_DEMPTY + 8 * (s == 0 ? D_ST - 1 : s - 1));
        if (b == 19 && tid == 0) mbar_arrive(bars + B_DSK);
        if (++s == D_ST) { s = 0; ph ^= 1; }
        if (s == 2) pa ^= 1;
      }
      WG_WAIT(0);
      fence_f(ag); fence_f(au);
      if ((tid & 127) == 0) { mbar_arrive(bars + B_DDONE); TLS(wg ? 2 : 1, wg ? 7 : 11); }
      mbar_wait(bars + B_SIDE, 0);
      if (wg == 1) mbar_wait(bars + B_DDONE, 0);
      else { mbar_wait(bars + B_DEMPTY + 16, 0); mbar_wait(bars + B_DEMPTY + 24, 0); }
      const float2 st0 = s_st[rl], st1 = s_st[rl + 8];
      const float ka[2] = {0.79788456f * st0.y, 0.79788456f * st1.y};
      const float kb[2] = {0.035677408f * st0.y * st0.y * st0.y, 0.035677408f * st1.y * st1.y * st1.y};
      const float kc[2] = {0.5f * st0.y * st0.y, 0.5f * st1.y * st1.y};
      const uint32_t ia = sbase + wg * 8192 + mrow;
      uint32_t w[48];
#pragma unroll
      for (int t = 0; t < 3; t++) {
#pragma unroll
        for (int g = 8 * t; g < 8 * t + 8; g++) {
          const float2 cg = *(const float2*)(s_cs + g * 8 + q * 2), cu = *(const float2*)(s_cs + 192 + g * 8 + q * 2);
          float r[4];
#pragma unroll
          for (int e = 0; e < 4; e++) {
            const float mu = e < 2 ? st0.x : st1.x;
            const float dg = ag[4 * g + e] - mu * ((e & 1) ? cg.y : cg.x);
            const float du = au[4 * g + e] - mu * ((e & 1) ? cu.y : cu.x);
            const float th = tanhf_(dg * fmaf(dg * dg, kb[e >> 1], ka[e >> 1]));
            r[e] = (dg * du) * fmaf(th, kc[e >> 1], kc[e >> 1]);
          }
          w[2 * g] = packbf(r[0], r[1]); w[2 * g + 1] = packbf(r[2], r[3]);
        }
#pragma unroll
        for (int c = 0; c < 4; c++) stsm4(ia + e_slot(t) + c * 2048, w[16 * t + 4 * c], w[16 * t + 4 * c + 1], w[16 * t + 4 * c + 2], w[16 * t + 4 * c + 3]);
        FENCE_ASYNC_SMEM();
        bar_arrive(3 + 3 * wg + t, 160);
      }
      bar_sync(9 + wg, 128);
      if ((tid & 127) == 0) TLS(wg ? 2 : 1, wg ? 8 : 12);
    }
    {
      float acc[40];
      const uint64_t da0 = mkdesc(sbase + wg * 8192, 1024, 128, 0), db0 = mkdesc(sbase + 16384, 1280, 128, 0);
      int s = 0, ph = 0, pa = 1;
#pragma unroll 1
      for (int kb = 0; kb < 24; kb++) {
        mbar_wait(bars + B_EFB + 8 * s, ph);
        if (s == 3) pa ^= 1;
        if (kb >= 3) mbar_wait(bars + B_EFA + 56 * wg + 8 * s, pa);
        if (kb == 3 && (tid & 127) == 0) TLS(wg ? 2 : 1, wg ? 10 : 13);
        const uint64_t da = da0 + (e_slot(s) >> 4), db = db0 + (e_slot(s) >> 4);
        WG_FENCE();
#pragma unroll
        for (int k = 0; k < 4; k++) wgmma_n80_ss<1>(acc, da + k * 128, db + k * 160, (kb | k) != 0);
        WG_COMMIT();
        WG_WAIT(1);
        if (kb > 0 && (tid & 127) == 0) mbar_arrive(bars + B_EEMPTY + 8 * (s == 0 ? E_ST - 1 : s - 1));
        if (++s == E_ST) { s = 0; ph ^= 1; }
      }
      WG_WAIT(0);
      fence_f(acc);
      if ((tid & 127) == 0) TLS(wg ? 2 : 1, wg ? 11 : 14);
      bar_sync(9 + wg, 128);
      const uint32_t oimg = sbase + e_slot(warp & 3) + wg * 8192;
      const uint32_t orow = oimg + (lane & 15) * 160 + (lane >> 4) * 16;
#pragma unroll
      for (int g2 = 0; g2 < 5; g2++) {
        uint32_t h0, h1, h2, h3;
        ldsm4(hw + mrow + g2 * 2048, h0, h1, h2, h3);
        const float* a = acc + 8 * g2;
        stsm4(orow + g2 * 32, packbf(a[0] + bflo(h0), a[1] + bfhi(h0)), packbf(a[2] + bflo(h1), a[3] + bfhi(h1)),
              packbf(a[4] + bflo(h2), a[5] + bfhi(h2)), packbf(a[6] + bflo(h3), a[7] + bfhi(h3)));
      }
      FENCE_ASYNC_SMEM();
      __syncwarp();
      if (elect_one()) { tma2d_store(&P.tmO, oimg, bj * 80, tok); BULK_COMMIT(); BULK_WAIT_READ(); }
      if (tid == 128) TLS(2, 12);
    }
  }
}

typedef CUresult (*EncodeFn)(CUtensorMap*, CUtensorMapDataType, cuuint32_t, void*, const cuuint64_t*, const cuuint64_t*, const cuuint32_t*,
                             const cuuint32_t*, CUtensorMapInterleave, CUtensorMapSwizzle, CUtensorMapL2promotion, CUtensorMapFloatOOBfill);

}

extern "C" void kernel_launch(void* const* d_in, const int* in_sizes, int n_in, void* d_out, int out_size) {
  static EncodeFn enc = nullptr;
  static void* qkv_ptr = nullptr;
  if (!enc) {
    void* fn = nullptr;
    cudaDriverEntryPointQueryResult qr;
    cudaGetDriverEntryPoint("cuTensorMapEncodeTiled", &fn, cudaEnableDefault, &qr);
    enc = (EncodeFn)fn;
    cudaGetSymbolAddress(&qkv_ptr, g_qkv);
    cudaFuncSetAttribute(fused_block, cudaFuncAttributeMaxDynamicSharedMemorySize, SMEM_BYTES);
  }
  Params P;
  P.x = (const __nv_bfloat16*)d_in[0];
  P.wqkv = (const __nv_bfloat16*)d_in[1];
  P.wg = (const __nv_bfloat16*)d_in[4];
  P.wu = (const __nv_bfloat16*)d_in[5];
  P.zero = 0;
  const cuuint32_t es[5] = {1, 1, 1, 1, 1};
  const CUtensorMapDataType BF = CU_TENSOR_MAP_DATA_TYPE_BFLOAT16;
  const CUtensorMapInterleave IL = CU_TENSOR_MAP_INTERLEAVE_NONE;
  const CUtensorMapL2promotion L2P = CU_TENSOR_MAP_L2_PROMOTION_L2_128B;
  const CUtensorMapFloatOOBfill OOB = CU_TENSOR_MAP_FLOAT_OOB_FILL_NONE;
  {
    cuuint64_t gd[2] = {640, 2048}, gs[1] = {1280};
    cuuint32_t bd[2] = {64, 256}, bo[2] = {80, 16};
    enc(&P.tmX, BF, 2, d_in[0], gd, gs, bd, es, IL, CU_TENSOR_MAP_SWIZZLE_128B, L2P, OOB);
    enc(&P.tmO, BF, 2, d_out, gd, gs, bo, es, IL, CU_TENSOR_MAP_SWIZZLE_NONE, L2P, OOB);
  }
  {
    cuuint64_t gd[3] = {8, 2048, 80}, gs[2] = {1280, 16};
    cuuint32_t bd[3] = {8, 64, 10};
    enc(&P.tmR, BF, 3, d_in[0], gd, gs, bd, es, IL, CU_TENSOR_MAP_SWIZZLE_NONE, L2P, OOB);
  }
  {
    cuuint64_t gd[3] = {64, 640, 30}, gs[2] = {3840, 128};
    cuuint32_t bd[3] = {64, 64, 2};
    enc(&P.tmW, BF, 3, d_in[1], gd, gs, bd, es, IL, CU_TENSOR_MAP_SWIZZLE_128B, L2P, OOB);
  }
  {
    cuuint64_t gd[2] = {256, 16 * 288}, gs[1] = {2048};
    cuuint32_t bd[2] = {32, 10};
    enc(&P.tmQ, CU_TENSOR_MAP_DATA_TYPE_UINT64, 2, qkv_ptr, gd, gs, bd, es, IL, CU_TENSOR_MAP_SWIZZLE_NONE, L2P, OOB);
  }
  {
    cuuint64_t gd[3] = {64, 640, 24}, gs[2] = {3072, 128};
    cuuint32_t bd[3] = {64, 32, 3};
    enc(&P.tmG, BF, 3, d_in[4], gd, gs, bd, es, IL, CU_TENSOR_MAP_SWIZZLE_128B, L2P, OOB);
    enc(&P.tmU, BF, 3, d_in[5], gd, gs, bd, es, IL, CU_TENSOR_MAP_SWIZZLE_128B, L2P, OOB);
  }
  {
    cuuint64_t gd[2] = {640, 640}, gs[1] = {1280};
    cuuint32_t bd[2] = {80, 64};
    enc(&P.tmWo, BF, 2, d_in[2], gd, gs, bd, es, IL, CU_TENSOR_MAP_SWIZZLE_NONE, L2P, OOB);
    gd[1] = 1536;
    enc(&P.tmWd, BF, 2, d_in[6], gd, gs, bd, es, IL, CU_TENSOR_MAP_SWIZZLE_NONE, L2P, OOB);
  }
  fused_block<<<132, 512, SMEM_BYTES, cudaStreamPerThread>>>(P);
}
```

```cpp
#include <cuda_runtime.h>
#include <cuda_bf16.h>
#include <cuda.h>
#include <stdint.h>

namespace {

constexpr int S_ = 2048, D_ = 640, F_ = 1536;
constexpr float LN_EPS = 1e-5f;
constexpr uint32_t POLY_MASK = 0xB6B6u;

__device__ __align__(1024) uint8_t g_qkv[16 * 288 * 2048];
__device__ __align__(1024) uint8_t g_o[16 * 80 * 2048];
__device__ __align__(1024) uint8_t g_h[16 * 80 * 2048];
__device__ __align__(1024) uint8_t g_H[16 * 192 * 2048];
__device__ __align__(1024) uint8_t g_wo[8 * 80 * 1280];
__device__ __align__(1024) uint8_t g_wd[8 * 192 * 1280];
__device__ uint4 g_st1[S_];
__device__ uint4 g_cs1[16 * 640];
__device__ __align__(16) float g_cs2[3072];
__device__ uint4 g_st2[S_ * 8];
__device__ unsigned g_flags[448 * 32];
constexpr int FL_DONE = 0, FL_PREP = 1, FL_PREP2 = 2, FL_IN = 3, FL_O = 4, FL_C = 36, FL_D = 68, FL_QKV = 192;

#define WG_FENCE() asm volatile("wgmma.fence.sync.aligned;" ::: "memory")
#define WG_COMMIT() asm volatile("wgmma.commit_group.sync.aligned;" ::: "memory")
#define WG_WAIT(n) asm volatile("wgmma.wait_group.sync.aligned %0;" ::"n"(n) : "memory")
__device__ __forceinline__ uint64_t mkdesc(uint32_t addr, uint32_t lbo, uint32_t sbo, int swz) {
  return (uint64_t)((addr & 0x3FFFF) >> 4) | ((uint64_t)(lbo >> 4) << 16) | ((uint64_t)(sbo >> 4) << 32) | ((uint64_t)swz << 62);
}
__device__ __forceinline__ uint32_t smem_u32(const void* p) { return (uint32_t)__cvta_generic_to_shared(p); }
__device__ __forceinline__ void mbar_init(uint32_t bar, int cnt) { asm volatile("mbarrier.init.shared::cta.b64 [%0], %1;" ::"r"(bar), "r"(cnt) : "memory"); }
__device__ __forceinline__ void mbar_expect(uint32_t bar, uint32_t bytes) { asm volatile("mbarrier.arrive.expect_tx.shared::cta.b64 _, [%0], %1;" ::"r"(bar), "r"(bytes) : "memory"); }
__device__ __forceinline__ void mbar_arrive(uint32_t bar) { asm volatile("mbarrier.arrive.shared::cta.b64 _, [%0];" ::"r"(bar) : "memory"); }
__device__ __forceinline__ void mbar_wait(uint32_t bar, uint32_t par) {
  asm volatile("{\n.reg .pred p;\n.reg .u32 c;\nmov.u32 c, 0;\nLW:\nmbarrier.try_wait.parity.shared::cta.b64 p, [%0], %1;\n@p bra.uni LD;\n"
               "add.u32 c, c, 1;\nsetp.lt.u32 p, c, 2000000;\n@p bra.uni LW;\ntrap;\nLD:\n}" ::"r"(bar), "r"(par) : "memory");
}
__device__ __forceinline__ bool mbar_test(uint32_t bar, uint32_t par) {
  uint32_t ok;
  asm volatile("{\n.reg .pred p;\nmbarrier.test_wait.parity.shared::cta.b64 p, [%1], %2;\nvote.sync.all.pred p, p, 0xffffffff;\nselp.u32 %0, 1, 0, p;\n}" : "=r"(ok) : "r"(bar), "r"(par) : "memory");
  return ok;
}
__device__ __forceinline__ void bulk_g2s(uint32_t dst, const void* src, uint32_t bytes, uint32_t bar) {
  asm volatile("cp.async.bulk.shared::cluster.global.mbarrier::complete_tx::bytes [%0], [%1], %2, [%3];" ::"r"(dst), "l"(src), "r"(bytes), "r"(bar) : "memory");
}
__device__ __forceinline__ void tma2d(uint32_t dst, const CUtensorMap* tm, int c0, int c1, uint32_t bar) {
  asm volatile("cp.async.bulk.tensor.2d.shared::cluster.global.mbarrier::complete_tx::bytes [%0], [%1, {%3, %4}], [%2];" ::"r"(dst), "l"(tm), "r"(bar), "r"(c0), "r"(c1) : "memory");
}
__device__ __forceinline__ void tma3d(uint32_t dst, const CUtensorMap* tm, int c0, int c1, int c2, uint32_t bar) {
  asm volatile("cp.async.bulk.tensor.3d.shared::cluster.global.mbarrier::complete_tx::bytes [%0], [%1, {%3, %4, %5}], [%2];" ::"r"(dst), "l"(tm), "r"(bar), "r"(c0), "r"(c1), "r"(c2) : "memory");
}
__device__ __forceinline__ void tm_prefetch(const CUtensorMap* tm) { asm volatile("prefetch.tensormap [%0];" ::"l"(tm) : "memory"); }
#define FENCE_ASYNC_GLOBAL() asm volatile("fence.proxy.async.global;" ::: "memory")
__device__ __forceinline__ void tma2d_store(const CUtensorMap* tm, uint32_t src, int c0, int c1) {
  asm volatile("cp.async.bulk.tensor.2d.global.shared::cta.bulk_group [%0, {%2, %3}], [%1];" ::"l"(tm), "r"(src), "r"(c0), "r"(c1) : "memory");
}
__device__ __forceinline__ void bulk_s2g(void* dst, uint32_t src, uint32_t bytes) {
  asm volatile("cp.async.bulk.global.shared::cta.bulk_group [%0], [%1], %2;" ::"l"(dst), "r"(src), "r"(bytes) : "memory");
}
__device__ __forceinline__ void l2_prefetch(const void* p, uint32_t bytes) { asm volatile("cp.async.bulk.prefetch.L2.global [%0], %1;" ::"l"(p), "r"(bytes) : "memory"); }
#define BULK_COMMIT() asm volatile("cp.async.bulk.commit_group;" ::: "memory")
#define BULK_WAIT() asm volatile("cp.async.bulk.wait_group 0;" ::: "memory")
#define BULK_WAIT_READ() asm volatile("cp.async.bulk.wait_group.read 0;" ::: "memory")
#define FENCE_ASYNC_SMEM() asm volatile("fence.proxy.async.shared::cta;" ::: "memory")
__device__ __forceinline__ void stsm4(uint32_t addr, uint32_t r0, uint32_t r1, uint32_t r2, uint32_t r3) {
  asm volatile("stmatrix.sync.aligned.m8n8.x4.shared.b16 [%0], {%1, %2, %3, %4};" ::"r"(addr), "r"(r0), "r"(r1), "r"(r2), "r"(r3));
}
__device__ __forceinline__ void ldsm4(uint32_t addr, uint32_t& r0, uint32_t& r1, uint32_t& r2, uint32_t& r3) {
  asm volatile("ldmatrix.sync.aligned.m8n8.x4.shared.b16 {%0, %1, %2, %3}, [%4];" : "=r"(r0), "=r"(r1), "=r"(r2), "=r"(r3) : "r"(addr) : "memory");
}
__device__ __forceinline__ bool elect_one() {
  uint32_t p;
  asm volatile("{\n.reg .pred e;\nelect.sync _|e, 0xffffffff;\nselp.u32 %0, 1, 0, e;\n}" : "=r"(p));
  return p;
}
__device__ __forceinline__ void bar_sync(int id, int n) { asm volatile("bar.sync %0, %1;" ::"r"(id), "r"(n) : "memory"); }
__device__ __forceinline__ void bar_arrive(int id, int n) { asm volatile("bar.arrive %0, %1;" ::"r"(id), "r"(n) : "memory"); }
__device__ __forceinline__ void flag_add(unsigned* f) { asm volatile("fence.acq_rel.gpu;\nred.relaxed.gpu.global.add.u32 [%0], 1;" ::"l"(f) : "memory"); }
__device__ __forceinline__ void flag_wait(const unsigned* f, unsigned n) {
  asm volatile("{\n.reg .pred p;\n.reg .u32 c, v;\nmov.u32 c, 0;\nFW:\nld.acquire.gpu.global.u32 v, [%0];\nsub.u32 v, v, %1;\nsetp.ge.s32 p, v, 0;\n@p bra.uni FD;\n"
               "add.u32 c, c, 1;\nsetp.lt.u32 p, c, 2000000;\n@p bra.uni FW;\ntrap;\nFD:\n}" ::"l"(f), "r"(n) : "memory");
}
__device__ __forceinline__ uint4 ldg128(const uint4* p) {
  uint4 v; asm volatile("ld.global.v4.u32 {%0, %1, %2, %3}, [%4];" : "=r"(v.x), "=r"(v.y), "=r"(v.z), "=r"(v.w) : "l"(p) : "memory"); return v;
}
__device__ __forceinline__ void flag_wait_warp(const unsigned* f, unsigned n) {
  asm volatile("{\n.reg .pred p;\n.reg .u32 c, v;\nmov.u32 c, 0;\nFW:\nld.acquire.gpu.global.u32 v, [%0];\nsub.u32 v, v, %1;\nsetp.ge.s32 p, v, 0;\n"
               "vote.sync.all.pred p, p, 0xffffffff;\n@p bra.uni FD;\nadd.u32 c, c, 1;\nsetp.lt.u32 p, c, 2000000;\n@p bra.uni FW;\ntrap;\nFD:\n}" ::"l"(f), "r"(n) : "memory");
}
__device__ __forceinline__ void st_tag(uint4* p, float a, float b, float c, unsigned tag) {
  asm volatile("{\n.reg .b128 v;\n.reg .b64 l, h;\nmov.b64 l, {%1, %2};\nmov.b64 h, {%3, %4};\nmov.b128 v, {l, h};\nst.relaxed.gpu.global.b128 [%0], v;\n}"
               ::"l"(p), "r"(__float_as_uint(a)), "r"(__float_as_uint(b)), "r"(__float_as_uint(c)), "r"(tag) : "memory");
}
__device__ __forceinline__ uint4 ld_tag(const uint4* p) {
  uint4 r;
  asm volatile("{\n.reg .b128 v;\n.reg .b64 l, h;\nld.relaxed.gpu.global.b128 v, [%4];\nmov.b128 {l, h}, v;\nmov.b64 {%0, %1}, l;\nmov.b64 {%2, %3}, h;\n}"
               : "=r"(r.x), "=r"(r.y), "=r"(r.z), "=r"(r.w) : "l"(p) : "memory");
  return r;
}
__device__ __forceinline__ float ex2f(float x) { float y; asm("ex2.approx.ftz.f32 %0, %1;" : "=f"(y) : "f"(x)); return y; }
__device__ __forceinline__ float tanhf_(float x) { float y; asm("tanh.approx.f32 %0, %1;" : "=f"(y) : "f"(x)); return y; }
__device__ __forceinline__ uint32_t packbf(float lo, float hi) { uint32_t r; asm("cvt.rn.bf16x2.f32 %0, %1, %2;" : "=r"(r) : "f"(hi), "f"(lo)); return r; }
__device__ __forceinline__ float bflo(uint32_t v) { return __uint_as_float(v << 16); }
__device__ __forceinline__ float bfhi(uint32_t v) { return __uint_as_float(v & 0xFFFF0000u); }
__device__ __forceinline__ float rbf(float x) { return bflo(packbf(x, 0.f)); }
__device__ __forceinline__ float ln_rstd(float var) {
  float r;
  asm("sqrt.approx.f32 %0, %1;" : "=f"(r) : "f"(rbf(rbf(var) + LN_EPS)));
  return __fdividef(1.f, rbf(r));
}
template <int N> __device__ __forceinline__ void fence_f(float (&a)[N]) {
#pragma unroll
  for (int i = 0; i < N; i++) asm volatile("" : "+f"(a[i])::"memory");
}
template <int N> __device__ __forceinline__ void fence_u(uint32_t (&a)[N]) {
#pragma unroll
  for (int i = 0; i < N; i++) asm volatile("" : "+r"(a[i])::"memory");
}

template<int TB> __device__ __forceinline__ void wgmma_n128_ss(float (&d)[64], uint64_t da, uint64_t db, int scale_d) {
  asm volatile("{\n.reg .pred p;\nsetp.ne.b32 p, %66, 0;\n"
    "wgmma.mma_async.sync.aligned.m64n128k16.f32.bf16.bf16 "
    "{%0, %1, %2, %3, %4, %5, %6, %7, %8, %9, %10, %11, %12, %13, %14, %15, %16, %17, %18, %19, %20, %21, %22, %23, "
    "%24, %25, %26, %27, %28, %29, %30, %31, %32, %33, %34, %35, %36, %37, %38, %39, %40, %41, %42, %43, %44, %45, %46, %47, "
    "%48, %49, %50, %51, %52, %53, %54, %55, %56, %57, %58, %59, %60, %61, %62, %63}, "
    "%64, %65, p, 1, 1, 0, %67;\n}\n"
    : "+f"(d[0]), "+f"(d[1]), "+f"(d[2]), "+f"(d[3]), "+f"(d[4]), "+f"(d[5]), "+f"(d[6]), "+f"(d[7]), "+f"(d[8]), "+f"(d[9]), "+f"(d[10]), "+f"(d[11]),
      "+f"(d[12]), "+f"(d[13]), "+f"(d[14]), "+f"(d[15]), "+f"(d[16]), "+f"(d[17]), "+f"(d[18]), "+f"(d[19]), "+f"(d[20]), "+f"(d[21]), "+f"(d[22]), "+f"(d[23]),
      "+f"(d[24]), "+f"(d[25]), "+f"(d[26]), "+f"(d[27]), "+f"(d[28]), "+f"(d[29]), "+f"(d[30]), "+f"(d[31]), "+f"(d[32]), "+f"(d[33]), "+f"(d[34]), "+f"(d[35]),
      "+f"(d[36]), "+f"(d[37]), "+f"(d[38]), "+f"(d[39]), "+f"(d[40]), "+f"(d[41]), "+f"(d[42]), "+f"(d[43]), "+f"(d[44]), "+f"(d[45]), "+f"(d[46]), "+f"(d[47]),
      "+f"(d[48]), "+f"(d[49]), "+f"(d[50]), "+f"(d[51]), "+f"(d[52]), "+f"(d[53]), "+f"(d[54]), "+f"(d[55]), "+f"(d[56]), "+f"(d[57]), "+f"(d[58]), "+f"(d[59]),
      "+f"(d[60]), "+f"(d[61]), "+f"(d[62]), "+f"(d[63])
    : "l"(da), "l"(db), "r"(scale_d), "n"(TB));
}
template<int TB> __device__ __forceinline__ void wgmma_n80_ss(float (&d)[40], uint64_t da, uint64_t db, int scale_d) {
  asm volatile("{\n.reg .pred p;\nsetp.ne.b32 p, %42, 0;\n"
    "wgmma.mma_async.sync.aligned.m64n80k16.f32.bf16.bf16 "
    "{%0, %1, %2, %3, %4, %5, %6, %7, %8, %9, %10, %11, %12, %13, %14, %15, %16, %17, %18, %19, %20, %21, %22, %23, "
    "%24, %25, %26, %27, %28, %29, %30, %31, %32, %33, %34, %35, %36, %37, %38, %39}, "
    "%40, %41, p, 1, 1, 0, %43;\n}\n"
    : "+f"(d[0]), "+f"(d[1]), "+f"(d[2]), "+f"(d[3]), "+f"(d[4]), "+f"(d[5]), "+f"(d[6]), "+f"(d[7]), "+f"(d[8]), "+f"(d[9]), "+f"(d[10]), "+f"(d[11]),
      "+f"(d[12]), "+f"(d[13]), "+f"(d[14]), "+f"(d[15]), "+f"(d[16]), "+f"(d[17]), "+f"(d[18]), "+f"(d[19]), "+f"(d[20]), "+f"(d[21]), "+f"(d[22]), "+f"(d[23]),
      "+f"(d[24]), "+f"(d[25]), "+f"(d[26]), "+f"(d[27]), "+f"(d[28]), "+f"(d[29]), "+f"(d[30]), "+f"(d[31]), "+f"(d[32]), "+f"(d[33]), "+f"(d[34]), "+f"(d[35]),
      "+f"(d[36]), "+f"(d[37]), "+f"(d[38]), "+f"(d[39])
    : "l"(da), "l"(db), "r"(scale_d), "n"(TB));
}
template<int TB> __device__ __forceinline__ void wgmma_n128_rs(float (&d)[64], uint32_t a0, uint32_t a1, uint32_t a2, uint32_t a3, uint64_t db) {
  asm volatile("{\n.reg .pred p;\nsetp.ne.b32 p, 1, 0;\n"
    "wgmma.mma_async.sync.aligned.m64n128k16.f32.bf16.bf16 "
    "{%0, %1, %2, %3, %4, %5, %6, %7, %8, %9, %10, %11, %12, %13, %14, %15, %16, %17, %18, %19, %20, %21, %22, %23, "
    "%24, %25, %26, %27, %28, %29, %30, %31, %32, %33, %34, %35, %36, %37, %38, %39, %40, %41, %42, %43, %44, %45, %46, %47, "
    "%48, %49, %50, %51, %52, %53, %54, %55, %56, %57, %58, %59, %60, %61, %62, %63}, "
    "{%64, %65, %66, %67}, %68, p, 1, 1, %69;\n}\n"
    : "+f"(d[0]), "+f"(d[1]), "+f"(d[2]), "+f"(d[3]), "+f"(d[4]), "+f"(d[5]), "+f"(d[6]), "+f"(d[7]), "+f"(d[8]), "+f"(d[9]), "+f"(d[10]), "+f"(d[11]),
      "+f"(d[12]), "+f"(d[13]), "+f"(d[14]), "+f"(d[15]), "+f"(d[16]), "+f"(d[17]), "+f"(d[18]), "+f"(d[19]), "+f"(d[20]), "+f"(d[21]), "+f"(d[22]), "+f"(d[23]),
      "+f"(d[24]), "+f"(d[25]), "+f"(d[26]), "+f"(d[27]), "+f"(d[28]), "+f"(d[29]), "+f"(d[30]), "+f"(d[31]), "+f"(d[32]), "+f"(d[33]), "+f"(d[34]), "+f"(d[35]),
      "+f"(d[36]), "+f"(d[37]), "+f"(d[38]), "+f"(d[39]), "+f"(d[40]), "+f"(d[41]), "+f"(d[42]), "+f"(d[43]), "+f"(d[44]), "+f"(d[45]), "+f"(d[46]), "+f"(d[47]),
      "+f"(d[48]), "+f"(d[49]), "+f"(d[50]), "+f"(d[51]), "+f"(d[52]), "+f"(d[53]), "+f"(d[54]), "+f"(d[55]), "+f"(d[56]), "+f"(d[57]), "+f"(d[58]), "+f"(d[59]),
      "+f"(d[60]), "+f"(d[61]), "+f"(d[62]), "+f"(d[63])
    : "r"(a0), "r"(a1), "r"(a2), "r"(a3), "l"(db), "n"(TB));
}
template<int TB> __device__ __forceinline__ void wgmma_n128_rs_z(float (&d)[64], uint32_t a0, uint32_t a1, uint32_t a2, uint32_t a3, uint64_t db) {
  asm volatile("{\n.reg .pred p;\nsetp.ne.b32 p, 0, 0;\n"
    "wgmma.mma_async.sync.aligned.m64n128k16.f32.bf16.bf16 "
    "{%0, %1, %2, %3, %4, %5, %6, %7, %8, %9, %10, %11, %12, %13, %14, %15, %16, %17, %18, %19, %20, %21, %22, %23, "
    "%24, %25, %26, %27, %28, %29, %30, %31, %32, %33, %34, %35, %36, %37, %38, %39, %40, %41, %42, %43, %44, %45, %46, %47, "
    "%48, %49, %50, %51, %52, %53, %54, %55, %56, %57, %58, %59, %60, %61, %62, %63}, "
    "{%64, %65, %66, %67}, %68, p, 1, 1, %69;\n}\n"
    : "=f"(d[0]), "=f"(d[1]), "=f"(d[2]), "=f"(d[3]), "=f"(d[4]), "=f"(d[5]), "=f"(d[6]), "=f"(d[7]), "=f"(d[8]), "=f"(d[9]), "=f"(d[10]), "=f"(d[11]),
      "=f"(d[12]), "=f"(d[13]), "=f"(d[14]), "=f"(d[15]), "=f"(d[16]), "=f"(d[17]), "=f"(d[18]), "=f"(d[19]), "=f"(d[20]), "=f"(d[21]), "=f"(d[22]), "=f"(d[23]),
      "=f"(d[24]), "=f"(d[25]), "=f"(d[26]), "=f"(d[27]), "=f"(d[28]), "=f"(d[29]), "=f"(d[30]), "=f"(d[31]), "=f"(d[32]), "=f"(d[33]), "=f"(d[34]), "=f"(d[35]),
      "=f"(d[36]), "=f"(d[37]), "=f"(d[38]), "=f"(d[39]), "=f"(d[40]), "=f"(d[41]), "=f"(d[42]), "=f"(d[43]), "=f"(d[44]), "=f"(d[45]), "=f"(d[46]), "=f"(d[47]),
      "=f"(d[48]), "=f"(d[49]), "=f"(d[50]), "=f"(d[51]), "=f"(d[52]), "=f"(d[53]), "=f"(d[54]), "=f"(d[55]), "=f"(d[56]), "=f"(d[57]), "=f"(d[58]), "=f"(d[59]),
      "=f"(d[60]), "=f"(d[61]), "=f"(d[62]), "=f"(d[63])
    : "r"(a0), "r"(a1), "r"(a2), "r"(a3), "l"(db), "n"(TB));
}
template<int TB> __device__ __forceinline__ void wgmma_n32_rs(float (&d)[16], uint32_t a0, uint32_t a1, uint32_t a2, uint32_t a3, uint64_t db) {
  asm volatile("{\n.reg .pred p;\nsetp.ne.b32 p, 1, 0;\n"
    "wgmma.mma_async.sync.aligned.m64n32k16.f32.bf16.bf16 "
    "{%0, %1, %2, %3, %4, %5, %6, %7, %8, %9, %10, %11, %12, %13, %14, %15}, "
    "{%16, %17, %18, %19}, %20, p, 1, 1, %21;\n}\n"
    : "+f"(d[0]), "+f"(d[1]), "+f"(d[2]), "+f"(d[3]), "+f"(d[4]), "+f"(d[5]), "+f"(d[6]), "+f"(d[7]), "+f"(d[8]), "+f"(d[9]), "+f"(d[10]), "+f"(d[11]),
      "+f"(d[12]), "+f"(d[13]), "+f"(d[14]), "+f"(d[15])
    : "r"(a0), "r"(a1), "r"(a2), "r"(a3), "l"(db), "n"(TB));
}
template<int TB> __device__ __forceinline__ void wgmma_n32_rs_z(float (&d)[16], uint32_t a0, uint32_t a1, uint32_t a2, uint32_t a3, uint64_t db) {
  asm volatile("{\n.reg .pred p;\nsetp.ne.b32 p, 0, 0;\n"
    "wgmma.mma_async.sync.aligned.m64n32k16.f32.bf16.bf16 "
    "{%0, %1, %2, %3, %4, %5, %6, %7, %8, %9, %10, %11, %12, %13, %14, %15}, "
    "{%16, %17, %18, %19}, %20, p, 1, 1, %21;\n}\n"
    : "=f"(d[0]), "=f"(d[1]), "=f"(d[2]), "=f"(d[3]), "=f"(d[4]), "=f"(d[5]), "=f"(d[6]), "=f"(d[7]), "=f"(d[8]), "=f"(d[9]), "=f"(d[10]), "=f"(d[11]),
      "=f"(d[12]), "=f"(d[13]), "=f"(d[14]), "=f"(d[15])
    : "r"(a0), "r"(a1), "r"(a2), "r"(a3), "l"(db), "n"(TB));
}
template<int TB> __device__ __forceinline__ void wgmma_n24_rs(float (&d)[12], uint32_t a0, uint32_t a1, uint32_t a2, uint32_t a3, uint64_t db) {
  asm volatile("{\n.reg .pred p;\nsetp.ne.b32 p, 1, 0;\n"
    "wgmma.mma_async.sync.aligned.m64n24k16.f32.bf16.bf16 "
    "{%0, %1, %2, %3, %4, %5, %6, %7, %8, %9, %10, %11}, "
    "{%12, %13, %14, %15}, %16, p, 1, 1, %17;\n}\n"
    : "+f"(d[0]), "+f"(d[1]), "+f"(d[2]), "+f"(d[3]), "+f"(d[4]), "+f"(d[5]), "+f"(d[6]), "+f"(d[7]), "+f"(d[8]), "+f"(d[9]), "+f"(d[10]), "+f"(d[11])
    : "r"(a0), "r"(a1), "r"(a2), "r"(a3), "l"(db), "n"(TB));
}

constexpr int A_ST = 4, A_A = 32768, A_STAGE = 49152;
constexpr int KV_BLK = 24576, Q_OFF = 196608;
constexpr int C_AOFF = 102400;
constexpr int D_ST = 6, D_STAGE = 32768, D_B = 24576;
constexpr int E_ST = 7, E_STAGE = 16384 + 10240;
constexpr int H_OFF = 200704;
constexpr int M_OFF = 221184;
constexpr int SMEM_BYTES = M_OFF + 8192 + 3072;
constexpr int B_AFULL = 0, B_KV = 40, B_Q = 104, B_WO = 120, B_EP = 128, B_CFULL = 136, B_CEMPTY = 216, B_DFB = 296, B_DFA = 344,
              B_EFB = 440, B_EFA = 496, B_FD = 552, B_O0 = 576, B_TWO = 640, B_AEMPTY = 640, B_DEMPTY = 672, B_EEMPTY = 720, B_CDONE = 776,
              B_DDONE = 784, B_MISC = 792, B_ASIDE = 792, B_AIMG = 800, B_PIECE = 808, B_NORM = 840, B_BDONE = 848, B_SIDE = 856, B_OD = 864,
              B_HPUB = 896, B_DEAD = 904, B_IMG = 920, B_AIMG2 = 936, B_HALF = 944, B_AF0 = 960, B_AF1 = 1008, B_AE0 = 1056;
__device__ __forceinline__ uint32_t e_slot(int s) { return 12288 + (s < 5 ? s + 2 : s - 5) * E_STAGE; }

constexpr int D_EARLY = 5, E_EARLY = 6;

struct Params {
  CUtensorMap tmX, tmW, tmQ, tmWo, tmWd, tmG, tmU, tmO, tmR;
  const __nv_bfloat16 *x, *wqkv, *wg, *wu;
  uint32_t zero;
};

__device__ __forceinline__ int ffn_bi(int c) { return (c >> 5) * 4 + (c & 1) + ((c >> 1) & 2); }
__device__ __forceinline__ int ffn_bj(int c) { return ((c >> 4) & 1) * 4 + ((c >> 1) & 1) + ((c >> 2) & 2); }
__device__ __forceinline__ uint32_t a_img(int m, int w) { return m ? (6 + 2 * (w / 3)) * 16384 + (w % 3) * 5120 : 11 * 16384 + w * 5120; }

__device__ __forceinline__ void store_piece(const CUtensorMap* tmQ, uint32_t sbase, int cta, int pc, int hf) {
  const int ti = (cta >> 6) * 4 + ((cta >> 2) & 3), tj = ((cta >> 4) & 3) * 4 + (cta & 3);
  const int r0 = tj % 5, o = hf * (9 + (r0 == 2)), p0 = (tj * 16 / 5) * 6 + r0 + (r0 > 2) + o;
#pragma unroll 1
  for (int w = 0; w < 4; w++) tma2d_store(tmQ, sbase + a_img(pc >> 1, (pc & 1) * 4 + w) + o * 256, ((pc & 1) * 4 + w) * 32, (ti * 2 + (pc >> 1)) * 288 + p0);
  BULK_COMMIT();
}

__device__ __forceinline__ uint32_t exp2_pair(float y0, float y1, uint32_t cm) {
  const uint32_t L = __byte_perm(__float_as_uint(y0), __float_as_uint(y1), 0x6521);
  uint32_t zh, E, r;
  asm("lop3.b32 %0, %1, %2, 0x3F003F00, 0xEA;" : "=r"(zh) : "r"(L), "r"(cm));
  asm("lop3.b32 %0, %1, %2, 0x00010001, 0xBA;" : "=r"(E) : "r"(L), "r"(cm));
  asm("fma.rn.bf16x2 %0, %1, %2, %3;" : "=r"(r) : "r"(L), "r"(zh), "r"(E));
  return r;
}
__device__ __forceinline__ void att_store(const float (&o)[12], int h, int grp, int row, int lane) {
  const int q = lane & 3, odd = h & 1, src = (lane & ~3) | (odd ? 0 : 2);
  const float l0 = __shfl_sync(0xffffffffu, odd ? o[0] : o[8], src), l1 = __shfl_sync(0xffffffffu, odd ? o[2] : o[10], src);
  float i0, i1;
  asm("rcp.approx.ftz.f32 %0, %1;" : "=f"(i0) : "f"(l0));
  asm("rcp.approx.ftz.f32 %0, %1;" : "=f"(i1) : "f"(l1));
  uint8_t* p = g_o + (grp * 80 + (h >> 1) * 5 + odd * 2) * 1024 + row * 16 + q * 4;
  asm volatile("{\n.reg .pred a, b;\nsetp.ne.u32 a, %7, 0;\nsetp.ne.u32 b, %8, 0;\n"
               "st.global.u32 [%0 + 1024], %3;\nst.global.u32 [%0 + 1152], %4;\n@a st.global.u32 [%0], %1;\n@a st.global.u32 [%0 + 128], %2;\n"
               "@b st.global.u32 [%0 + 2048], %5;\n@b st.global.u32 [%0 + 2176], %6;\n}"
               ::"l"(p), "r"(packbf(o[0] * i0, o[1] * i0)), "r"(packbf(o[2] * i1, o[3] * i1)), "r"(packbf(o[4] * i0, o[5] * i0)),
                 "r"(packbf(o[6] * i1, o[7] * i1)), "r"(packbf(o[8] * i0, o[9] * i0)), "r"(packbf(o[10] * i1, o[11] * i1)),
                 "r"((int)(!odd || q >= 2)), "r"((int)(odd || q < 2)) : "memory");
}
__device__ __forceinline__ void load_q(uint32_t (&q)[8], const uint8_t* sm, int pass, int tid, uint32_t zero) {
  const uint8_t* qp = sm + Q_OFF + pass * 12288 + (tid >> 8) * 6144 + (((tid >> 5) & 7) * 16 + ((tid & 31) >> 2)) * 16 + (tid & 3) * 4;
  q[0] = *(const uint32_t*)(qp); q[1] = *(const uint32_t*)(qp + 128);
  q[2] = *(const uint32_t*)(qp + 2048); q[3] = *(const uint32_t*)(qp + 2048 + 128);
  q[4] = *(const uint32_t*)(qp + 4096); q[5] = *(const uint32_t*)(qp + 4096 + 128);
  q[6] = q[0] & zero; q[7] = q[1] & zero;
}
__device__ __forceinline__ const unsigned* qkv_flag(int cta, int m, int part) {
  const int lane = threadIdx.x & 31;
  const int c0 = (part == 4 ? 0 : (lane & 4) ? 1280 : 640) + (cta >> 2) * 20 + (lane & 1) * 19;
  return g_flags + (FL_QKV + ((part < 4 ? part : cta & 3) * 4 + m + (lane & 2)) * 16 + (c0 >> 7)) * 32;
}
__device__ __forceinline__ void load_qkv(uint32_t sbase, uint32_t bars, int cta, int m, int part, bool gate) {
  const int h = cta >> 2, tb = (part < 4 ? part : cta & 3) * 4 + m;
  if (gate) mbar_wait(bars + (part ? B_KV : B_AIMG), 0);
  if (elect_one()) {
    FENCE_ASYNC_GLOBAL();
    const uint8_t* src = g_qkv + tb * 589824 + h * 6144;
    if (part == 4) {
      mbar_expect(bars + B_Q + 8 * m, 12288);
      bulk_g2s(sbase + Q_OFF + m * 12288, src, 6144, bars + B_Q + 8 * m);
      bulk_g2s(sbase + Q_OFF + m * 12288 + 6144, src + 2 * 589824, 6144, bars + B_Q + 8 * m);
    } else {
      const uint32_t dst = sbase + (4 * m + part) * KV_BLK, fb = bars + B_KV + 8 * (4 * m + part);
      mbar_expect(fb, KV_BLK);
#pragma unroll
      for (int c = 0; c < 4; c++) bulk_g2s(dst + c * 6144, src + (c >> 1) * 2 * 589824 + (1 + (c & 1)) * 196608, 6144, fb);
    }
  }
}
__device__ __forceinline__ void load_wo(const CUtensorMap* tmR, uint32_t sbase, uint32_t bars, int cta, uint32_t gate) {
  mbar_wait(bars + gate, 0);
  if (elect_one()) {
    FENCE_ASYNC_GLOBAL();
    mbar_expect(bars + B_WO, 102400 + 20480);
    const int bi = ffn_bi(cta), bj = ffn_bj(cta);
    bulk_g2s(sbase, g_wo + bj * 102400, 102400, bars + B_WO);
    const int tok = (bi >> 1) * 256 + (bi & 1) * 64;
    tma3d(sbase + H_OFF, tmR, 0, tok, bj * 10, bars + B_WO);
    tma3d(sbase + H_OFF + 10240, tmR, 0, tok + 128, bj * 10, bars + B_WO);
  }
}
__device__ __forceinline__ bool att_safe(uint32_t bars, volatile unsigned* s_max) {
  mbar_wait(bars + B_NORM, 0);
  return __all_sync(0xffffffffu, __uint_as_float(s_max[0]) * __uint_as_float(s_max[1]) <= 4096.f);
}

__device__ __forceinline__ bool attention(const CUtensorMap* tmQ, const CUtensorMap* tmR, uint8_t* sm, uint32_t sbase, uint32_t bars, uint32_t zero, unsigned ep, int cta, unsigned* pub) {
  const int tid = threadIdx.x, wid = __shfl_sync(0xffffffffu, tid >> 5, 0), lane = tid & 31, wg = wid >> 2;
  const int h = cta >> 2, quarter = cta & 3;
  volatile unsigned* s_max = (volatile unsigned*)(sm + M_OFF + 8000);
  const uint32_t cm = 0x007F007Fu | zero;
  const uint64_t dk0 = mkdesc(sbase, 2048, 128, 0), dv0 = mkdesc(sbase + 6144, 128, 2048, 0);
  const int grp = (quarter * 4 + wg) * 2, row = (wid & 3) * 16 + (lane >> 2);
  uint32_t q[8];
  float o[12];
  const unsigned chores = wg == 2 ? 0x0003 : wid == 4 ? 0x0204 : wg == 1 ? 0x0004 : wid == 12 ? 0x2000 : 0;
  const unsigned* pfp = wg == 1 ? qkv_flag(cta, 1, (wid & 3) == 3 && (lane & 8) ? 4 : wid & 3) : g_flags + ((lane & 1) ? FL_O + ffn_bi(cta) * 2 : FL_PREP) * 32;
  unsigned pf = 0;
#pragma unroll 1
  for (int pass = 0; pass < 2; pass++) {
    mbar_wait(bars + B_Q + 8 * pass, 0);
    load_q(q, sm, pass, tid, zero);
#pragma unroll
    for (int i = 0; i < 12; i++) o[i] = 0.f;
    fence_u(q); fence_f(o);
    uint64_t dk = dk0, dv = dv0;
#pragma unroll 1
    for (int j = pass * 8; j < pass * 8 + 8; j++) {
      if (j < 8) mbar_wait(bars + B_KV + 8 * j, 0);
#pragma unroll
      for (int u = 0; u < 2; u++) {
        if (u == 0 && ((chores >> j) & 1)) asm volatile("ld.relaxed.gpu.global.u32 %0, [%1];" : "=r"(pf) : "l"(pfp) : "memory");
        float s[64];
        WG_FENCE();
        wgmma_n128_rs_z<0>(s, q[0], q[1], q[2], q[3], dk + u * 768);
        wgmma_n128_rs<0>(s, q[4], q[5], q[6], q[7], dk + u * 768 + 256);
        WG_COMMIT();
        WG_WAIT(0);
        fence_f(s);
#pragma unroll
        for (int v = 0; v < 2; v++) {
          constexpr int G = 8;
          uint32_t p[2 * G];
#pragma unroll
          for (int i = 0; i < G; i++) {
            const int g = v * G + i;
            if ((POLY_MASK >> g) & 1) {
              p[2 * i] = exp2_pair(s[4 * g], s[4 * g + 1], cm);
              p[2 * i + 1] = exp2_pair(s[4 * g + 2], s[4 * g + 3], cm);
            } else {
              p[2 * i] = packbf(ex2f(s[4 * g]), ex2f(s[4 * g + 1]));
              p[2 * i + 1] = packbf(ex2f(s[4 * g + 2]), ex2f(s[4 * g + 3]));
            }
          }
          fence_u(p);
          WG_FENCE();
#pragma unroll
          for (int c = 0; c < G / 2; c++) wgmma_n24_rs<1>(o, p[4 * c], p[4 * c + 1], p[4 * c + 2], p[4 * c + 3], dv + u * 768 + (v * G / 2 + c) * 16);
          WG_COMMIT();
        }
        WG_WAIT(0);
      }
      dk += KV_BLK >> 4; dv += KV_BLK >> 4;
      if ((j & 13) == 12 && (tid & 127) == 0) mbar_arrive(bars + B_DEAD + 4 * (j & 2));
      if ((chores >> j) & 1) {
        if (j == 0) {
          if (pub) {
            mbar_wait(bars + B_PIECE + 16 + 8 * (wid & 1), 0);
            if (elect_one()) store_piece(tmQ, sbase, cta + j, 2 + (wid & 1), (wid >> 1) & 1);
          }
        } else if (j == 1) {
          if (elect_one()) {
            BULK_WAIT();
            mbar_arrive(bars + B_AIMG2);
            if (pub) asm volatile("fence.acq_rel.gpu;\nred.relaxed.gpu.global.add.u32 [%0], 1;" ::"l"(pub) : "memory");
          }
        } else if (j == 2) {
          mbar_wait(bars + B_AIMG2, 0);
          if (!__all_sync(0xffffffffu, (int)(pf - 4 * ep) >= 0)) flag_wait_warp(pfp, 4 * ep);
#pragma unroll 1
          for (int i = (wid & 3) == 3 ? 0 : 1; i < 2; i++) load_qkv(sbase, bars, cta, 1, i ? wid & 3 : 4, false);
        } else if (att_safe(bars, s_max)) {
          if (j == 9) {
            if (lane < 4) asm volatile("fence.acq_rel.gpu;\nred.relaxed.gpu.global.add.u32 [%0], 4;" ::"l"(g_flags + (FL_O + (quarter * 4 + lane) * 2) * 32) : "memory");
          }
          else {
            const unsigned n = ((lane & 1) ? 128 : 32) * ep;
            if (!__all_sync(0xffffffffu, (int)(pf - n) >= 0)) flag_wait_warp(pfp, n);
            load_wo(tmR, sbase, bars, cta, B_DEAD);
          }
        }
        __syncwarp();
      }
    }
    fence_f(o);
    att_store(o, h, grp + pass, row, lane);
    if (pass == 0) {
      mbar_wait(bars + B_Q + 8, 0);
      unsigned km = 0, qm = 0;
#pragma unroll
      for (int r = 0; r < 5; r++) {
        const uint8_t* p = r < 4 ? sm + wid * 12288 + (r * 32 + lane) * 16 : sm + Q_OFF + (wid >> 2) * 6144 + ((wid & 3) * 32 + lane) * 16;
        const uint4 a = *(const uint4*)(p + (h & 1) * 4096), b = *(const uint4*)(p + 2048);
        const uint2 c = *(const uint2*)(p + ((h & 1) ? 8 : 4096));
        const uint32_t w[10] = {a.x, a.y, a.z, a.w, b.x, b.y, b.z, b.w, c.x, c.y};
        uint32_t n2 = 0;
#pragma unroll
        for (int e = 0; e < 10; e++) asm("fma.rn.bf16x2 %0, %1, %1, %0;" : "+r"(n2) : "r"(w[e]));
        float n = bflo(n2) + bfhi(n2);
        if ((POLY_MASK >> (r * 4 + (lane >> 3))) & 1) n *= 0.25f;
        km = max(km, qm);
        qm = __float_as_uint(n);
      }
      asm volatile("red.shared.max.u32 [%0], %1;\nred.shared.max.u32 [%0 + 4], %2;" ::"r"(sbase + M_OFF + 8000), "r"(qm), "r"(km) : "memory");
      __syncwarp();
      if (lane == 0) mbar_arrive(bars + B_NORM);
    }
  }
  const bool safe = att_safe(bars, s_max);
  if (!safe) {
#pragma unroll 1
    for (int pass = 0; pass < 2; pass++) {
      load_q(q, sm, pass, tid, zero);
      if (h & 1) { if (!(lane & 2)) { q[0] = 0; q[1] = 0; } } else if (lane & 2) { q[4] = 0; q[5] = 0; }
      fence_u(q);
#pragma unroll
      for (int i = 0; i < 12; i++) o[i] = 0.f;
      float m0 = -INFINITY, m1 = -INFINITY;
#pragma unroll 1
      for (int j = 0; j < 64; j++) {
        float s[16]; uint32_t p[8];
        const int off = (j >> 2) * 768 + (j & 3) * 32;
        WG_FENCE();
        wgmma_n32_rs_z<0>(s, q[0], q[1], q[2], q[3], dk0 + off);
        wgmma_n32_rs<0>(s, q[4], q[5], q[6], q[7], dk0 + off + 256);
        WG_COMMIT();
        WG_WAIT(0);
        fence_f(s);
        float n0 = m0, n1 = m1;
#pragma unroll
        for (int g = 0; g < 4; g++) {
          const float sc = ((POLY_MASK >> ((j & 3) * 4 + g)) & 1) ? 0.5f : 1.f;
          s[4 * g] *= sc; s[4 * g + 1] *= sc; s[4 * g + 2] *= sc; s[4 * g + 3] *= sc;
          n0 = fmaxf(n0, fmaxf(s[4 * g], s[4 * g + 1])); n1 = fmaxf(n1, fmaxf(s[4 * g + 2], s[4 * g + 3]));
        }
        n0 = fmaxf(n0, __shfl_xor_sync(0xffffffffu, n0, 1)); n0 = fmaxf(n0, __shfl_xor_sync(0xffffffffu, n0, 2));
        n1 = fmaxf(n1, __shfl_xor_sync(0xffffffffu, n1, 1)); n1 = fmaxf(n1, __shfl_xor_sync(0xffffffffu, n1, 2));
        const float a0 = ex2f(m0 - n0), a1 = ex2f(m1 - n1);
        m0 = n0; m1 = n1;
#pragma unroll
        for (int i = 0; i < 3; i++) { o[4 * i] *= a0; o[4 * i + 1] *= a0; o[4 * i + 2] *= a1; o[4 * i + 3] *= a1; }
#pragma unroll
        for (int g = 0; g < 4; g++) {
          p[2 * g] = packbf(ex2f(s[4 * g] - m0), ex2f(s[4 * g + 1] - m0));
          p[2 * g + 1] = packbf(ex2f(s[4 * g + 2] - m1), ex2f(s[4 * g + 3] - m1));
        }
        fence_u(p); fence_f(o);
        WG_FENCE();
#pragma unroll
        for (int c = 0; c < 2; c++) wgmma_n24_rs<1>(o, p[4 * c], p[4 * c + 1], p[4 * c + 2], p[4 * c + 3], dv0 + off + c * 16);
        WG_COMMIT();
        WG_WAIT(0);
        fence_f(o);
      }
      att_store(o, h, grp + pass, row, lane);
    }
  }
  if ((wid & 3) == 0) {
    int ord = 0;
    if (lane == 0) {
      asm volatile("atom.shared.add.u32 %0, [%1], 1;" : "=r"(ord) : "r"(sbase + M_OFF + 8012) : "memory");
      mbar_arrive(bars + B_BDONE);
    }
    ord = __shfl_sync(0xffffffffu, ord, 0);
    if (safe && (ord == 0 || ord == 3)) {
      mbar_wait(bars + B_DEAD + 8, 0);
      if (elect_one()) {
        FENCE_ASYNC_GLOBAL();
#pragma unroll 1
        for (int kb = ord ? 4 : 0; kb < (ord ? 5 : 4); kb++) {
          mbar_expect(bars + B_CFULL + 8 * kb, 16384);
          bulk_g2s(sbase + C_AOFF + kb * 16384, g_o + (ffn_bi(cta) * 160 + kb * 16) * 1024, 16384, bars + B_CFULL + 8 * kb);
        }
      }
    }
  }
  __syncwarp();
  if (wg == 0 && safe) {
    if (lane == 0) mbar_arrive(bars + B_O0 + 8 * wid);
  } else {
    const bool both = wg == 1 && safe && mbar_test(bars + B_O0 + 8 * (wid & 3), 0);
    __threadfence();
    __syncwarp();
    if (lane < 2 && (lane || !safe || both)) asm volatile("red.relaxed.gpu.global.add.u32 [%0], 1;" ::"l"(g_flags + (FL_O + grp + (lane ? 1 : both ? -1 : 0)) * 32) : "memory");
    if (wg == 1 && safe && !both) {
      mbar_wait(bars + B_O0 + 8 * (wid & 3), 0);
      if (lane == 0) flag_add(g_flags + (FL_O + grp - 1) * 32);
    }
  }
  if (!safe && wid == 12) { flag_wait_warp(g_flags + FL_PREP * 32, 32 * ep); load_wo(tmR, sbase, bars, cta, B_BDONE); }
  __syncwarp();
  return safe;
}

__device__ __forceinline__ void prep(const Params& P, uint8_t* sm, uint32_t sbase, uint32_t bars, int pb) {
  const int tid = threadIdx.x, warp = tid >> 5, lane = tid & 31;
  unsigned ep = 0;
  if (tid == 0) {
    ep = (__ldcg(g_flags + FL_DONE * 32) >> 7) + 1;
    asm volatile("red.relaxed.gpu.global.add.u32 [%0], 1;" ::"l"(g_flags + FL_IN * 32) : "memory");
  }
  __nanosleep(3000);
  if (warp >= 8) {
    const uint32_t bar = bars + (warp - 8) * 16, boff = 16384 + (warp - 8) * 20480;
    if (lane == 0) { mbar_init(bar, 1); mbar_init(bar + 8, 1); asm volatile("fence.mbarrier_init.release.cluster;" ::: "memory"); }
    const int u0 = pb * 8 + warp - 8;
#pragma unroll 1
    for (int n = 0; u0 + 32 * (n - 1) < 272; n++) {
      const int u = u0 + 32 * n;
      __syncwarp();
      if (u < 272 && lane == 0) {
        const bool isd = u >= 80;
        const int v = isd ? u - 80 : u, j = isd ? v / 24 : v / 10, kb = v - j * (isd ? 24 : 10);
        mbar_expect(bar + 8 * (n & 1), 10240);
        tma2d(sbase + boff + (n & 1) * 10240, isd ? &P.tmWd : &P.tmWo, j * 80, kb * 64, bar + 8 * (n & 1));
      }
      if (n > 0) {
        const int m = n - 1, w = u - 32;
        mbar_wait(bar + 8 * (m & 1), (m >> 1) & 1);
        uint4* dst = (uint4*)(w >= 80 ? g_wd + (w - 80) * 10240 : g_wo + w * 10240);
        const uint8_t* src = sm + boff + (m & 1) * 10240;
#pragma unroll 4
        for (int i = lane; i < 640; i += 32) {
          const int g = i >> 3, kc = g / 10, nn = g - kc * 10;
          dst[i] = *(const uint4*)(src + (kc * 8 + (i & 7)) * 160 + nn * 16);
        }
        if (m == 2) { __syncwarp(); if (lane == 0) flag_add(g_flags + FL_PREP * 32); }
      }
    }
  } else if (warp < 6) {
    float* part = (float*)sm;
    const int ch = tid % 96, rg = tid / 96;
    const __nv_bfloat16* src = (pb < 2 ? P.wg : P.wu) + (pb & 1) * 768 + ch * 8 + (size_t)rg * 320 * F_;
    float a[8];
#pragma unroll
    for (int e = 0; e < 8; e++) a[e] = 0.f;
#pragma unroll 1
    for (int r0 = 0; r0 < 320; r0 += 16) {
      uint4 wv[16];
#pragma unroll
      for (int r = 0; r < 16; r++) wv[r] = __ldg((const uint4*)(src + (size_t)(r0 + r) * F_));
#pragma unroll
      for (int r = 0; r < 16; r++) {
        a[0] += bflo(wv[r].x); a[1] += bfhi(wv[r].x); a[2] += bflo(wv[r].y); a[3] += bfhi(wv[r].y);
        a[4] += bflo(wv[r].z); a[5] += bfhi(wv[r].z); a[6] += bflo(wv[r].w); a[7] += bfhi(wv[r].w);
      }
    }
    *(float4*)(part + rg * 768 + ch * 8) = make_float4(a[0], a[1], a[2], a[3]);
    *(float4*)(part + rg * 768 + ch * 8 + 4) = make_float4(a[4], a[5], a[6], a[7]);
    bar_sync(1, 192);
    const float4 p0 = *(float4*)(part + tid * 4), p1 = *(float4*)(part + 768 + tid * 4);
    *(float4*)(g_cs2 + pb * 768 + tid * 4) = make_float4(p0.x + p1.x, p0.y + p1.y, p0.z + p1.z, p0.w + p1.w);
  } else if (warp == 6 && lane < 30) {
    l2_prefetch((const uint8_t*)(pb < 2 ? P.wg : P.wu) + (pb & 1) * 983040 + lane * 32768, 32768);
  }
  __syncthreads();
  if (tid == 0) {
    flag_add(g_flags + FL_PREP2 * 32);
    flag_wait(g_flags + FL_IN * 32, 132 * ep);
  }
}

__global__ void __launch_bounds__(512, 1) fused_block(const __grid_constant__ Params P) {
  extern __shared__ __align__(1024) uint8_t sm[];
  float* s_cs = (float*)(sm + M_OFF);
  float2* s_st = (float2*)(sm + M_OFF + 8192);
  float* s_part = (float*)(sm + M_OFF + 2560);
  volatile unsigned* s_ep = (volatile unsigned*)(sm + M_OFF + 8016);
  const uint32_t sbase = smem_u32(sm), bars = sbase + M_OFF + 6784, himg = sbase + H_OFF;
  const int tid = threadIdx.x, warp = __shfl_sync(0xffffffffu, tid >> 5, 0), lane = tid & 31;
  if (tid == 32) { tm_prefetch(&P.tmW); tm_prefetch(&P.tmX); }
  int cta = blockIdx.x;
  uint32_t nsm;
  asm volatile("mov.u32 %0, %%nsmid;" : "=r"(nsm));
  if (nsm == 132) {
    uint32_t smid;
    asm volatile("mov.u32 %0, %%smid;" : "=r"(smid));
    const int t = smid >> 1, u = t - 32, u7 = (u * 37) >> 8;
    const int r0 = ((t + 7) & 7) * 8 + (t >> 3), r1 = (u - u7 * 7) * 8 + 4 + u7, r2 = t < 62 ? t + 4 : t - 2;
    const int r = t < 32 ? r0 : t < 60 ? r1 : r2;
    cta = r * 2 + (smid & 1);
  }
  if (cta >= 128) { prep(P, sm, sbase, bars, cta - 128); return; }
  const int bi = ffn_bi(cta), bj = ffn_bj(cta);
  const int ti = (cta >> 6) * 4 + ((cta >> 2) & 3), tj = ((cta >> 4) & 3) * 4 + (cta & 3);
  const int own = (80 * bj + 16) >> 5;

  if (warp == 0 && elect_one()) {
#pragma unroll
    for (int s = 0; s < A_ST; s++) mbar_init(bars + B_AFULL + 8 * s, 1);
    asm volatile("fence.mbarrier_init.release.cluster;" ::: "memory");
#pragma unroll 1
    for (int kb = 0; kb < (tj < 15 ? A_ST : 0); kb++) {
      const uint32_t st = sbase + kb * A_STAGE, fb = bars + B_AFULL + 8 * kb;
      mbar_expect(fb, A_STAGE);
      tma3d(st + A_A, &P.tmW, 0, kb * 64, tj * 2, fb);
      tma2d(st, &P.tmX, kb * 64, ti * 256, fb);
      tma2d(st + 16384, &P.tmX, kb * 64, ti * 256 + 128, fb);
    }
  }
  __syncwarp();
  if (warp >= 12) {
    asm volatile("setmaxnreg.dec.sync.aligned.u32 48;");
    unsigned ep;
    if (warp == 12) {
      if (elect_one()) {
#pragma unroll
        for (int i = 0; i < 18; i++) mbar_init(bars + B_AF0 + 8 * i, i < 12 ? 1 : 2);
        asm volatile("fence.mbarrier_init.release.cluster;" ::: "memory");
      }
      __syncwarp();
    } else if (warp == 13) {
      if (elect_one()) {
#pragma unroll 13
        for (int i = B_KV; i < B_DFA + 8; i += 8) mbar_init(bars + i, 1);
        mbar_init(bars + B_ASIDE, 128); mbar_init(bars + B_AIMG, 2); mbar_init(bars + B_IMG, 2); mbar_init(bars + B_AIMG2, 4);
        mbar_init(bars + B_HALF, 4); mbar_init(bars + B_HALF + 8, 4); mbar_init(bars + B_NORM, 16); mbar_init(bars + B_BDONE, 4);
        mbar_init(bars + B_SIDE, 32); mbar_init(bars + B_HPUB, 1); mbar_init(bars + B_DEAD, 4); mbar_init(bars + B_DEAD + 8, 4);
        asm volatile("fence.mbarrier_init.release.cluster;" ::: "memory");
      }
      __syncwarp();
    } else if (warp == 14) {
      if (elect_one()) {
#pragma unroll 8
        for (int i = B_DFA + 8; i < B_O0 + 32; i += 8) mbar_init(bars + i, 1);
#pragma unroll
        for (int i = B_TWO; i < B_MISC; i += 8) mbar_init(bars + i, 2);
#pragma unroll
        for (int i = 0; i < 4; i++) { mbar_init(bars + B_PIECE + 8 * i, 4); mbar_init(bars + B_OD + 8 * i, 1); }
        *(uint4*)(sm + M_OFF + 8000) = make_uint4(0, 0, 0, 0);
        asm volatile("fence.mbarrier_init.release.cluster;" ::: "memory");
      }
      __syncwarp();
    } else ep = __ldcg(g_flags + FL_DONE * 32);
    __syncthreads();
    if (tid == 480) {
      *s_ep = (ep >> 7) + 1; mbar_arrive(bars + B_EP);
      asm volatile("red.relaxed.gpu.global.add.u32 [%0], 1;" ::"l"(g_flags + FL_IN * 32) : "memory");
      tm_prefetch(&P.tmQ); tm_prefetch(&P.tmG); tm_prefetch(&P.tmU); tm_prefetch(&P.tmO); tm_prefetch(&P.tmR);
    }
    if (warp == 12) {
      if (tj < 15) {
#pragma unroll 1
        for (int n = 0; n < 18; n++) {
          const int k = n < 12 ? n >> 1 : n - 12;
          mbar_wait(bars + (n < 12 ? B_AEMPTY + 8 * (n / 3) : B_AE0 + 8 * k), 0);
          if (elect_one()) {
            if (n >= 12) {
              mbar_expect(bars + B_AF1 + 8 * k, 16384);
              tma2d(sbase + (k < 5 ? 2 * k + 1 : 1) * 16384, &P.tmX, (k + 4) * 64, ti * 256 + 128, bars + B_AF1 + 8 * k);
            } else if (n & 1) {
              tma2d(sbase + n * 16384, &P.tmX, (k + 4) * 64, ti * 256, bars + B_AF0 + 8 * k);
            } else {
              mbar_expect(bars + B_AF0 + 8 * k, 32768);
              tma3d(sbase + n * 16384, &P.tmW, 0, (k + 4) * 64, tj * 2, bars + B_AF0 + 8 * k);
            }
          }
        }
      }
    }
    mbar_wait(bars + B_EP, 0);
    ep = *s_ep;
    if (tj < 15) mbar_wait(bars + B_IMG, 0); else __nanosleep(3000);
#pragma unroll 1
    for (int i = warp == 15 ? 0 : 1; i < 2; i++) {
      flag_wait_warp(qkv_flag(cta, 0, i ? warp - 12 : 4), 2 * ep);
      load_qkv(sbase, bars, cta, 0, i ? warp - 12 : 4, i && (tj < 15 || warp > 12));
    }
    asm volatile("setmaxnreg.inc.sync.aligned.u32 128;");
  } else if (warp >= 8) {
    __syncthreads();
    {
      const int t = tid - 256, sw = warp - 8;
      mbar_wait(bars + B_EP, 0);
      const unsigned ep = *s_ep;
      if (tj < 15) mbar_wait(bars + B_AFULL, 0);
      {
        uint4 wv[10], xv[10];
        const uint4* wp = (const uint4*)(P.wqkv + (size_t)(bi * 40 + sw * 10) * 1920 + bj * 240) + min(lane, 29);
        const uint4* xp = (const uint4*)(P.x + (size_t)(bi * 128 + bj * 16 + sw * 4 + (lane >> 3)) * D_) + (lane & 7);
#pragma unroll
        for (int r = 0; r < 10; r++) { xv[r] = ldg128(xp + r * 8); wv[r] = ldg128(wp + r * 240); }
        float s1 = 0.f, s2 = 0.f, s3 = 0.f, s4 = 0.f, a[8];
#pragma unroll
        for (int e = 0; e < 8; e++) a[e] = 0.f;
#pragma unroll
        for (int r = 0; r < 10; r++) {
          const uint32_t xw[4] = {xv[r].x, xv[r].y, xv[r].z, xv[r].w};
#pragma unroll
          for (int e = 0; e < 4; e++) {
            const float d0 = bflo(xw[e]), d1 = bfhi(xw[e]);
            s1 += d0; s3 += d1; s2 = fmaf(d0, d0, s2); s4 = fmaf(d1, d1, s4);
          }
          a[0] += bflo(wv[r].x); a[1] += bfhi(wv[r].x); a[2] += bflo(wv[r].y); a[3] += bfhi(wv[r].y);
          a[4] += bflo(wv[r].z); a[5] += bfhi(wv[r].z); a[6] += bflo(wv[r].w); a[7] += bfhi(wv[r].w);
        }
        if (lane < 30) {
          *(float4*)(s_part + sw * 240 + lane * 8) = make_float4(a[0], a[1], a[2], a[3]);
          *(float4*)(s_part + sw * 240 + lane * 8 + 4) = make_float4(a[4], a[5], a[6], a[7]);
        }
        s1 += s3; s2 += s4;
#pragma unroll
        for (int o = 4; o; o >>= 1) { s1 += __shfl_xor_sync(0xffffffffu, s1, o); s2 += __shfl_xor_sync(0xffffffffu, s2, o); }
        s1 *= (1.f / D_);
        if ((lane & 7) == 0) st_tag(g_st1 + bi * 128 + bj * 16 + sw * 4 + (lane >> 3), rbf(s1), ln_rstd(fmaxf(s2 * (1.f / D_) - s1 * s1, 0.f)), 0.f, ep);
      }
      bar_sync(2, 128);
      if (t < 80) {
        const float* p = s_part + t * 3;
        st_tag(g_cs1 + bi * 640 + bj * 80 + t, (p[0] + p[240]) + (p[480] + p[720]), (p[1] + p[241]) + (p[481] + p[721]), (p[2] + p[242]) + (p[482] + p[722]), ep);
      }
      if (tj < 15) {
        const int w0 = tj * 128 / 3, dl = tj * 128 - 3 * w0;
        uint4 sv, sw2, v[16];
        const uint4* cp = g_cs1 + min(w0 + t, 639);
        mbar_wait(bars + B_AE0, 0);
#pragma unroll 1
        for (int it = 0;; it++) {
          sv = ld_tag(g_st1 + ti * 256 + t); sw2 = ld_tag(g_st1 + ti * 256 + 128 + t);
          unsigned bad = (sv.w ^ ep) | (sw2.w ^ ep);
          if (t < 44) {
#pragma unroll
            for (int r = 0; r < 16; r++) v[r] = ld_tag(cp + r * 640);
#pragma unroll
            for (int r = 0; r < 16; r++) bad |= v[r].w ^ ep;
          }
          if (!__any_sync(0xffffffffu, bad)) break;
          if (it > 1000000) __trap();
        }
        s_st[t] = make_float2(__uint_as_float(sv.x), __uint_as_float(sv.y));
        s_st[t + 128] = make_float2(__uint_as_float(sw2.x), __uint_as_float(sw2.y));
        if (t < 44) {
          float c0 = 0.f, c1 = 0.f, c2 = 0.f;
#pragma unroll
          for (int r = 0; r < 16; r++) { c0 += __uint_as_float(v[r].x); c1 += __uint_as_float(v[r].y); c2 += __uint_as_float(v[r].z); }
          float* p = s_cs + 2 + t * 3 - dl;
          p[0] = c0; p[1] = c1; p[2] = c2;
        }
      }
      mbar_arrive(bars + B_ASIDE);
      if (tj < 15 && sw < 2) {
#pragma unroll 1
        for (int hf = 0; hf < 2; hf++) {
          mbar_wait(bars + (hf ? B_PIECE : B_HALF) + 8 * sw, 0);
          if (elect_one()) store_piece(&P.tmQ, sbase, cta, sw, hf);
        }
        if (elect_one()) {
          BULK_WAIT();
          mbar_arrive(bars + B_IMG);
          flag_add(g_flags + (FL_QKV + ti * 32 + tj) * 32);
        }
      }
      __syncwarp();
    }
  } else {
    asm volatile("setmaxnreg.inc.sync.aligned.u32 168;");
    const int wg = warp >> 2, q = lane & 3;
    __syncthreads();
    if (tj < 15) {
      float ac[2][64];
      const uint64_t da0 = mkdesc(sbase + wg * 8192, 16, 1024, 1), db0 = mkdesc(sbase + A_A, 8192, 1024, 1);
#pragma unroll 1
      for (int kb = 0; kb < 4; kb++) {
        const int s = kb;
        mbar_wait(bars + B_AFULL + 8 * s, 0);
        const uint64_t da = da0 + s * (A_STAGE >> 4), db = db0 + s * (A_STAGE >> 4);
        WG_FENCE();
#pragma unroll
        for (int k = 0; k < 4; k++) {
          wgmma_n128_ss<1>(ac[0], da + k * 2, db + k * 128, (kb | k) != 0);
          wgmma_n128_ss<1>(ac[1], da + k * 2 + 1024, db + k * 128, (kb | k) != 0);
        }
        WG_COMMIT();
        WG_WAIT(1);
        if (kb > 0 && (tid & 127) == 0) mbar_arrive(bars + B_AEMPTY + 8 * ((kb - 1) & 3));
      }
      const int ty = tj / 5, g0 = (7 - tj + ty * 5) % 5;
      const uint32_t pad = ty == 0 ? ((q & 1) ? 0x00003F80u : 0x3F803F80u) : ty == 1 ? ((q & 1) ? 0x0000BB73u : 0xC04B4440u) : ((q & 1) ? 0u : 0x00003F80u);
#pragma unroll
      for (int m = 0; m < 2; m++) {
#pragma unroll 1
        for (int k6 = 0; k6 < 6; k6++) {
          mbar_wait(bars + (m ? B_AF1 : B_AF0) + 8 * k6, 0);
          const uint64_t da = da0 + (m && k6 == 5 ? 1 : 2 * k6 + 1) * 1024, db = db0 + (k6 - 1) * 2048;
          WG_FENCE();
#pragma unroll
          for (int k = 0; k < 4; k++) wgmma_n128_ss<1>(ac[m], da + k * 2, db + k * 128, 1);
          WG_COMMIT();
          WG_WAIT(1);
          if ((tid & 127) == 0) {
            if (k6 == 0) { if (m == 0) mbar_arrive(bars + B_AEMPTY + 24); }
            else if (m == 0) mbar_arrive(bars + B_AE0 + 8 * (k6 - 1));
            else if (k6 == 1) mbar_arrive(bars + B_AE0 + 40);
          }
        }
        if (m == 0) mbar_wait(bars + B_ASIDE, 0);
        const int rw = warp * 16;
        const float2 st0 = s_st[m * 128 + rw + (lane >> 2)], st1 = s_st[m * 128 + rw + (lane >> 2) + 8];
        const bool mu0 = ty == 1 && !((POLY_MASK >> (rw >> 3)) & 1), mu1 = ty == 1 && !((POLY_MASK >> ((rw >> 3) + 1)) & 1);
        const float sc = ty == 0 ? 0.32259642f : ty == 1 ? 2.f : 1.f;
        float c0 = mu0 ? st0.y : st0.y * sc, c1 = mu1 ? st1.y : st1.y * sc;
        uint32_t pd0 = mu0 ? 0u : pad, pd1 = mu1 ? 0u : pad;
        uint8_t* ib = sm + a_img(m, warp) + lane * 4;
        float2 cs[16];
#pragma unroll
        for (int g = 0; g < 6; g++) cs[g] = *(const float2*)(s_cs + 2 + g * 8 + q * 2);
        uint8_t* ip = ib + g0 * 256 + (q < 2 ? 256 : 0);
        asm volatile("" : "+f"(c0), "+f"(c1), "+r"(pd0), "+r"(pd1)::"memory");
        WG_WAIT(0);
        fence_f(ac[0]); fence_f(ac[1]);
        bar_sync(7, 256);
        if (m == 1 && (tid & 127) == 0) {
          mbar_arrive(bars + B_AIMG);
        }
#pragma unroll
        for (int i = 0; i < 4; i++)
          if (i < 3 || g0 == 0) { *(uint32_t*)(ip + i * 1536) = pd0; *(uint32_t*)(ip + i * 1536 + 128) = pd1; }
#pragma unroll
        for (int g = 0; g < 16; g++) {
          if (g + 6 < 16) cs[g + 6] = *(const float2*)(s_cs + 2 + (g + 6) * 8 + q * 2);
          const float* a = ac[m] + 4 * g;
          uint8_t* p = ib + (g % 5 >= g0 + (q < 2) ? 256 : 0) + (g + g / 5) * 256;
          *(uint32_t*)p = packbf((a[0] - st0.x * cs[g].x) * c0, (a[1] - st0.x * cs[g].y) * c0);
          *(uint32_t*)(p + 128) = packbf((a[2] - st1.x * cs[g].x) * c1, (a[3] - st1.x * cs[g].y) * c1);
          if (m == 0 && g == 8) {
            FENCE_ASYNC_SMEM();
            __syncwarp();
            if (lane == 0) mbar_arrive(bars + B_HALF + 8 * wg);
          }
        }
        FENCE_ASYNC_SMEM();
        __syncwarp();
        if (lane == 0) mbar_arrive(bars + B_PIECE + 8 * (m * 2 + wg));
      }
    }
    asm volatile("setmaxnreg.dec.sync.aligned.u32 128;");
  }
  mbar_wait(bars + B_EP, 0);
  const unsigned ep = *s_ep;
  const bool safe = attention(&P.tmQ, &P.tmR, sm, sbase, bars, P.zero, ep, cta, tj < 15 ? g_flags + (FL_QKV + ti * 32 + 16 + tj) * 32 : nullptr);
  if (warp >= 12) {
    asm volatile("setmaxnreg.dec.sync.aligned.u32 24;");
    if (warp < 14) {
      const int w = warp - 12;
      bar_sync(1 + w, 160);
      if (elect_one()) {
        bulk_s2g(g_h + ((bi * 2 + w) * 80 + bj * 10) * 1024, himg + w * 10240, 10240);
        BULK_COMMIT(); BULK_WAIT();
        flag_add(g_flags + (FL_C + bi * 2 + w) * 32);
        if (w == 1) { mbar_arrive(bars + B_HPUB); }
      }
      __syncwarp();
    }
    if (warp > 12) {
      const int t = warp - 13;
      bar_sync(3 + t, 288);
      if (elect_one()) {
        bulk_s2g(g_H + (bi * 24 + bj * 3 + t) * 16384, sbase + e_slot(t), 16384);
        BULK_COMMIT(); BULK_WAIT();
        mbar_arrive(bars + B_OD + 8 * t);
        flag_add(g_flags + (FL_D + bi * 3 + t) * 32);
        if (t == 1) mbar_arrive(bars + B_OD + 24);
      }
    } else {
#pragma unroll 1
      for (int t = 1; t < 3; t++) {
        mbar_wait(bars + B_OD + 8 * t, 0);
        flag_wait_warp(g_flags + (FL_D + bi * 3 + t) * 32, 8 * ep);
        if (lane == 0) mbar_arrive(bars + B_FD + 8 * t);
      }
    }
  } else if (warp >= 8) {
    asm volatile("setmaxnreg.dec.sync.aligned.u32 40;");
    if (warp == 8) {
      if (elect_one()) {
        int s = 0, ph = 1;
#pragma unroll 1
        for (int b = 0; b < 20; b++) {
          const int kb = b < 2 ? own + b : b - 2 + (b - 2 >= own ? 2 : 0);
          if (b < 2) { mbar_wait(bars + B_CEMPTY + 8 + 8 * b, 0); mbar_wait(bars + B_CEMPTY + 48 + 8 * b, 0); }
          else if (b == 2) mbar_wait(bars + B_CDONE, 0);
          else if (b == D_EARLY) mbar_wait(bars + B_HPUB, 0);
          else if (b >= D_ST) mbar_wait(bars + B_DEMPTY + 8 * s, ph);
          mbar_expect(bars + B_DFB + 8 * s, D_B);
          tma3d(sbase + s * D_STAGE, &P.tmG, 0, kb * 32, bj * 3, bars + B_DFB + 8 * s);
          tma3d(sbase + s * D_STAGE + 12288, &P.tmU, 0, kb * 32, bj * 3, bars + B_DFB + 8 * s);
          if (++s == D_ST) { s = 0; ph ^= 1; }
        }
        flag_wait(g_flags + FL_PREP2 * 32, 4 * ep);
        FENCE_ASYNC_GLOBAL();
        mbar_wait(bars + B_DEMPTY + 16, 0); mbar_wait(bars + B_DEMPTY + 24, 0);
        const uint8_t* wsrc = g_wd + bj * 192 * 1280;
        int t = -1, d = 4;
        s = 0; ph = 1;
#pragma unroll 1
        for (int u = 0; u < 24; u++) {
          const int kb = u < 3 ? 3 * bj + u : 3 * (d + (d >= bj)) + t;
          if (u == 2) mbar_wait(bars + B_DDONE, 0);
          if (u == E_EARLY) mbar_wait(bars + B_OD + 24, 0);
          if (u >= E_ST) mbar_wait(bars + B_EEMPTY + 8 * s, ph);
          mbar_expect(bars + B_EFB + 8 * s, 10240);
          bulk_g2s(sbase + e_slot(s) + 16384, wsrc + kb * 10240, 10240, bars + B_EFB + 8 * s);
          if (++s == E_ST) { s = 0; ph ^= 1; }
          if (++d == 7) { d = 0; t++; }
        }
        asm volatile("red.relaxed.gpu.global.add.u32 [%0], 1;" ::"l"(g_flags + FL_DONE * 32) : "memory");
      }
    } else if (warp < 11) {
      if (elect_one()) {
        const int w = warp - 9, grp = bi * 2 + w;
        if (w || !safe) flag_wait(g_flags + (FL_O + grp) * 32, 128 * ep);
        mbar_wait(bars + B_BDONE, 0);
        FENCE_ASYNC_GLOBAL();
#pragma unroll 1
        for (int kb = w || !safe ? 0 : 5; kb < 5; kb++) {
          const uint32_t fb = bars + B_CFULL + 40 * w + 8 * kb;
          if (w && kb) mbar_wait(bars + B_CEMPTY + 8 * (kb - 1), 0);
          mbar_expect(fb, 16384);
          bulk_g2s(sbase + C_AOFF + (w ? (kb ? kb - 1 : 5) : kb) * 16384, g_o + (grp * 80 + kb * 16) * 1024, 16384, fb);
        }
        flag_wait(g_flags + (FL_C + grp) * 32, 8 * ep);
        mbar_wait(bars + B_CDONE, 0);
        FENCE_ASYNC_GLOBAL();
        {
          int s = 2, ph = 1;
#pragma unroll 1
          for (int b = 2; b < 20; b++) {
            const uint32_t fb = bars + B_DFA + 48 * w + 8 * s;
            if (b >= D_ST) mbar_wait(bars + B_DEMPTY + 8 * s, ph);
            mbar_expect(fb, 4096);
            bulk_g2s(sbase + s * D_STAGE + D_B + w * 4096, g_h + (grp * 80 + (b - 2 + (b - 2 >= own ? 2 : 0)) * 4) * 1024, 4096, fb);
            if (++s == D_ST) { s = 0; ph ^= 1; }
          }
        }
        if (w == 0) {
          int s = 3, ph = 1;
#pragma unroll 1
          for (int t = 0; t < 3; t++) {
            if (t == 0) { flag_wait(g_flags + (FL_D + bi * 3) * 32, 8 * ep); mbar_wait(bars + B_DDONE, 0); }
            else mbar_wait(bars + B_FD + 8 * t, 0);
            FENCE_ASYNC_GLOBAL();
#pragma unroll 1
            for (int d = 0; d < 7; d++) {
              const uint32_t fb = bars + B_EFA + 8 * s;
              if (t == 0 && d + 3 == E_EARLY) mbar_wait(bars + B_OD + 24, 0);
              if (t > 0 || d >= 4) {
                if (t == 0) mbar_wait(bars + B_OD + 8 * s, 0);
                mbar_wait(bars + B_EEMPTY + 8 * s, ph);
              }
              mbar_expect(fb, 16384);
              bulk_g2s(sbase + e_slot(s), g_H + (bi * 24 + 3 * (d + (d >= bj)) + t) * 16384, 16384, fb);
              if (++s == E_ST) { s = 0; ph ^= 1; }
            }
          }
        }
      }
    } else {
      flag_wait_warp(g_flags + FL_PREP2 * 32, 4 * ep);
#pragma unroll 1
      for (int c = lane; c < 96; c += 32) *(float4*)(s_cs + c * 4) = __ldcg((const float4*)(g_cs2 + (c < 48 ? 0 : F_ - 192) + bj * 192 + c * 4));
      mbar_wait(bars + B_DFA + 48 + 16, 0);
#pragma unroll 1
      for (int r = lane; r < 128; r += 32) {
        float m0, s1, s2, m2;
        const uint4* p = g_st2 + bi * 1024 + r;
#pragma unroll 1
        for (int it = 0;; it++) {
          unsigned bad = 0;
          s1 = 0.f; s2 = 0.f; m2 = 0.f;
#pragma unroll 1
          for (int c0 = 0; c0 < 8; c0 += 4) {
            uint4 v[4];
#pragma unroll
            for (int c = 0; c < 4; c++) v[c] = ld_tag(p + (c0 + c) * 128);
            if (c0 == 0) m0 = __uint_as_float(v[0].x);
#pragma unroll
            for (int c = 0; c < 4; c++) {
              const float d = __uint_as_float(v[c].x) - m0;
              s1 += d; s2 = fmaf(d, d, s2); m2 += __uint_as_float(v[c].y); bad |= v[c].w ^ ep;
            }
          }
          if (!__any_sync(0xffffffffu, bad)) break;
          if (it > 1000000) __trap();
        }
        s1 *= 0.125f;
        s_st[r] = make_float2(rbf(m0 + s1), ln_rstd((m2 + 80.f * fmaxf(s2 - 8.f * s1 * s1, 0.f)) * (1.f / D_)));
      }
      mbar_arrive(bars + B_SIDE);
    }
  } else {
    const int wg = warp >> 2, q = lane & 3;
    const int rl = warp * 16 + (lane >> 2);
    const int tok = ((bi >> 1) * 2 + wg) * 128 + (bi & 1) * 64 + (warp & 3) * 16;
    const uint32_t mrow = (lane >> 4) * 1024 + ((warp & 3) * 16 + (lane & 15)) * 16;
    const uint32_t hw = himg + wg * 10240;
    {
      uint32_t xr[20];
      float acc[40];
      const uint64_t da0 = mkdesc(sbase + C_AOFF, 1024, 128, 0), db0 = mkdesc(sbase, 1280, 128, 0);
      mbar_wait(bars + B_WO, 0);
#pragma unroll
      for (int g = 0; g < 5; g++) ldsm4(hw + mrow + g * 2048, xr[4 * g], xr[4 * g + 1], xr[4 * g + 2], xr[4 * g + 3]);
#pragma unroll 1
      for (int kb = 0; kb < 5; kb++) {
        mbar_wait(bars + B_CFULL + 40 * wg + 8 * kb, 0);
        const uint64_t da = da0 + (wg ? (kb ? kb - 1 : 5) : kb) * 1024, db = db0 + kb * 1280;
        WG_FENCE();
#pragma unroll
        for (int k = 0; k < 8; k++) wgmma_n80_ss<1>(acc, da + k * 128, db + k * 160, (kb | k) != 0);
        WG_COMMIT();
        WG_WAIT(1);
        if (kb > 0 && (tid & 127) == 0) mbar_arrive(bars + B_CEMPTY + 40 * wg + 8 * (kb - 1));
      }
      WG_WAIT(0);
      fence_f(acc);
      if ((tid & 127) == 0) { mbar_arrive(bars + B_CDONE); }
      float s0 = 0.f, s1 = 0.f;
#pragma unroll
      for (int g = 0; g < 10; g++) {
        xr[2 * g] = packbf(acc[4 * g] + bflo(xr[2 * g]), acc[4 * g + 1] + bfhi(xr[2 * g]));
        xr[2 * g + 1] = packbf(acc[4 * g + 2] + bflo(xr[2 * g + 1]), acc[4 * g + 3] + bfhi(xr[2 * g + 1]));
        if (g & 1) stsm4(hw + mrow + (g - 1) * 1024, xr[2 * g - 2], xr[2 * g - 1], xr[2 * g], xr[2 * g + 1]);
      }
      FENCE_ASYNC_SMEM();
      bar_sync(1 + wg, 160);
#pragma unroll
      for (int g = 0; g < 10; g++) {
        acc[4 * g] = bflo(xr[2 * g]); acc[4 * g + 1] = bfhi(xr[2 * g]); acc[4 * g + 2] = bflo(xr[2 * g + 1]); acc[4 * g + 3] = bfhi(xr[2 * g + 1]);
        s0 += acc[4 * g] + acc[4 * g + 1]; s1 += acc[4 * g + 2] + acc[4 * g + 3];
      }
      s0 += __shfl_xor_sync(0xffffffffu, s0, 1); s1 += __shfl_xor_sync(0xffffffffu, s1, 1);
      s0 += __shfl_xor_sync(0xffffffffu, s0, 2); s1 += __shfl_xor_sync(0xffffffffu, s1, 2);
      s0 *= (1.f / 80.f); s1 *= (1.f / 80.f);
      float q0 = 0.f, q1 = 0.f;
#pragma unroll
      for (int g = 0; g < 10; g++) {
        float d;
        d = acc[4 * g] - s0; q0 += d * d; d = acc[4 * g + 1] - s0; q0 += d * d;
        d = acc[4 * g + 2] - s1; q1 += d * d; d = acc[4 * g + 3] - s1; q1 += d * d;
      }
      q0 += __shfl_xor_sync(0xffffffffu, q0, 1); q1 += __shfl_xor_sync(0xffffffffu, q1, 1);
      q0 += __shfl_xor_sync(0xffffffffu, q0, 2); q1 += __shfl_xor_sync(0xffffffffu, q1, 2);
      if (q < 2) st_tag(g_st2 + (bi * 8 + bj) * 128 + rl + q * 8, q ? s1 : s0, q ? q1 : q0, 0.f, ep);
    }
    asm volatile("setmaxnreg.inc.sync.aligned.u32 224;");
    {
      float ac[3][64];
      const uint64_t da0 = mkdesc(sbase + D_B + wg * 4096, 1024, 128, 0), db0 = mkdesc(sbase, 12288, 1024, 1);
      const uint64_t dah = mkdesc(hw + (bj & 1) * 2048, 1024, 128, 0);
      int s = 0, ph = 0, pa = 1;
#pragma unroll 1
      for (int b = 0; b < 16; b++) {
        mbar_wait(bars + B_DFB + 8 * s, ph);
        if (b >= 2) mbar_wait(bars + B_DFA + 48 * wg + 8 * s, pa);
        const uint64_t da = b < 2 ? dah + b * 256 : da0 + s * (D_STAGE >> 4), db = db0 + s * (D_STAGE >> 4);
        WG_FENCE();
#pragma unroll
        for (int k = 0; k < 2; k++) {
#pragma unroll
          for (int t = 0; t < 3; t++) wgmma_n128_ss<1>(ac[t], da + k * 128, db + k * 128 + t * 256, (b | k) != 0);
        }
        WG_COMMIT();
        WG_WAIT(1);
        if (b > 0 && (tid & 127) == 0) mbar_arrive(bars + B_DEMPTY + 8 * (s == 0 ? D_ST - 1 : s - 1));
        if (++s == D_ST) { s = 0; ph ^= 1; }
        if (s == 2) pa ^= 1;
      }
#pragma unroll 1
      for (int i = 0; i < 4; i++) {
        const int st = i < 2 ? i + 4 : i - 2;
        mbar_wait(bars + B_DFB + 8 * st, i >> 1);
        mbar_wait(bars + B_DFA + 48 * wg + 8 * st, 0);
        const uint64_t da = da0 + st * (D_STAGE >> 4), db = db0 + st * (D_STAGE >> 4);
        WG_FENCE();
#pragma unroll
        for (int k = 0; k < 2; k++) wgmma_n128_ss<1>(ac[0], da + k * 128, db + k * 128, 1);
        WG_COMMIT();
      }
      WG_WAIT(0);
      if ((tid & 127) == 0) mbar_arrive(bars + B_DEMPTY + 24);
      fence_f(ac[0]); fence_f(ac[1]); fence_f(ac[2]);
      mbar_wait(bars + B_SIDE, 0);
      mbar_wait(bars + B_DEMPTY + 16, 0);
      const float2 st0 = s_st[rl], st1 = s_st[rl + 8];
      const float ka[2] = {0.79788456f * st0.y, 0.79788456f * st1.y};
      const float kb[2] = {0.035677408f * st0.y * st0.y * st0.y, 0.035677408f * st1.y * st1.y * st1.y};
      const uint32_t ia = sbase + wg * 8192 + mrow;
      uint32_t w[48];
#pragma unroll
      for (int t = 0; t < 3; t++) {
        if (t == 1) {
#pragma unroll 1
          for (int i = 0; i < 4; i++) {
            const int st = i < 2 ? i + 4 : i - 2;
            const uint64_t da = da0 + st * (D_STAGE >> 4), db = db0 + st * (D_STAGE >> 4) + 256;
            WG_FENCE();
#pragma unroll
            for (int k = 0; k < 2; k++) {
              wgmma_n128_ss<1>(ac[1], da + k * 128, db + k * 128, 1);
              wgmma_n128_ss<1>(ac[2], da + k * 128, db + k * 128 + 256, 1);
            }
            WG_COMMIT();
          }
          WG_WAIT(0);
          fence_f(ac[1]); fence_f(ac[2]);
          if ((tid & 127) == 0) { mbar_arrive(bars + B_DDONE); }
          mbar_wait(bars + B_DEMPTY + 24, 0);
        }
        float* x = ac[t];
#pragma unroll
        for (int g = 0; g < 8; g++) {
          const float2 cg = *(const float2*)(s_cs + (8 * t + g) * 8 + q * 2), cu = *(const float2*)(s_cs + 192 + (8 * t + g) * 8 + q * 2);
#pragma unroll
          for (int e = 0; e < 4; e++) {
            const float mu = e < 2 ? st0.x : st1.x;
            x[4 * g + e] -= mu * ((e & 1) ? cg.y : cg.x);
            x[32 + 4 * g + e] -= mu * ((e & 1) ? cu.y : cu.x);
          }
        }
#pragma unroll
        for (int i = 0; i < 32; i++) {
          const float dg = x[i];
          x[32 + i] *= dg;
          x[i] = tanhf_(dg * fmaf(dg * dg, kb[(i >> 1) & 1], ka[(i >> 1) & 1]));
        }
#pragma unroll
        for (int i = 0; i < 16; i++) {
          w[16 * t + i] = packbf(fmaf(x[32 + 2 * i], x[2 * i], x[32 + 2 * i]), fmaf(x[33 + 2 * i], x[2 * i + 1], x[33 + 2 * i]));
        }
        if (t == 2) mbar_wait(bars + B_DDONE, 0);
#pragma unroll
        for (int c = 0; c < 4; c++) stsm4(ia + e_slot(t) + c * 2048, w[16 * t + 4 * c], w[16 * t + 4 * c + 1], w[16 * t + 4 * c + 2], w[16 * t + 4 * c + 3]);
        FENCE_ASYNC_SMEM();
        bar_arrive(3 + t, 288);
      }
      bar_sync(9 + wg, 128);
    }
    {
      float acc[40];
      const float k0 = 0.5f * s_st[rl].y * s_st[rl].y, k1 = 0.5f * s_st[rl + 8].y * s_st[rl + 8].y;
      uint64_t da0 = mkdesc(sbase + wg * 8192, 1024, 128, 0), db0 = mkdesc(sbase + 16384, 1280, 128, 0);
      const uint32_t fa = bars + B_EFA;
#pragma unroll
      for (int s = 0; s < 3; s++) {
        mbar_wait(bars + B_EFB + 8 * s, 0);
        WG_FENCE();
#pragma unroll
        for (int k = 0; k < 4; k++) wgmma_n80_ss<1>(acc, da0 + (e_slot(s) >> 4) + k * 128, db0 + (e_slot(s) >> 4) + k * 160, (s | k) != 0);
        WG_COMMIT();
        WG_WAIT(1);
        if (s > 0 && (tid & 127) == 0) mbar_arrive(bars + B_EEMPTY + 8 * (s - 1));
      }
#pragma unroll 1
      for (int r = 0; r < 3; r++) {
        da0 += P.zero; db0 += P.zero;
#pragma unroll
        for (int i = 0; i < E_ST; i++) {
          const int s = i < 4 ? i + 3 : i - 4;
          mbar_wait(bars + B_EFB + 8 * s, (r ^ (i >= 4)) & 1);
          mbar_wait(fa + 8 * s, r & 1);
          WG_FENCE();
#pragma unroll
          for (int k = 0; k < 4; k++) wgmma_n80_ss<1>(acc, da0 + (e_slot(s) >> 4) + k * 128, db0 + (e_slot(s) >> 4) + k * 160, 1);
          WG_COMMIT();
          WG_WAIT(1);
          if ((tid & 127) == 0) mbar_arrive(bars + B_EEMPTY + 8 * (s == 0 ? E_ST - 1 : s - 1));
        }
      }
      uint32_t hr[20];
#pragma unroll
      for (int g = 0; g < 5; g++) ldsm4(hw + mrow + g * 2048, hr[4 * g], hr[4 * g + 1], hr[4 * g + 2], hr[4 * g + 3]);
      const uint32_t oimg = sbase + e_slot(3 + (warp & 3)) + wg * 8192;
      const uint32_t orow = oimg + (lane & 15) * 160 + (lane >> 4) * 16;
      bar_sync(9 + wg, 128);
      WG_WAIT(0);
      fence_f(acc);
#pragma unroll
      for (int g2 = 0; g2 < 5; g2++) {
        const float* a = acc + 8 * g2;
        const uint32_t h0 = hr[4 * g2], h1 = hr[4 * g2 + 1], h2 = hr[4 * g2 + 2], h3 = hr[4 * g2 + 3];
        stsm4(orow + g2 * 32, packbf(fmaf(a[0], k0, bflo(h0)), fmaf(a[1], k0, bfhi(h0))), packbf(fmaf(a[2], k1, bflo(h1)), fmaf(a[3], k1, bfhi(h1))),
              packbf(fmaf(a[4], k0, bflo(h2)), fmaf(a[5], k0, bfhi(h2))), packbf(fmaf(a[6], k1, bflo(h3)), fmaf(a[7], k1, bfhi(h3))));
      }
      FENCE_ASYNC_SMEM();
      __syncwarp();
      if (elect_one()) { tma2d_store(&P.tmO, oimg, bj * 80, tok); BULK_COMMIT(); BULK_WAIT_READ(); }
    }
  }
}

typedef CUresult (*EncodeFn)(CUtensorMap*, CUtensorMapDataType, cuuint32_t, void*, const cuuint64_t*, const cuuint64_t*, const cuuint32_t*,
                             const cuuint32_t*, CUtensorMapInterleave, CUtensorMapSwizzle, CUtensorMapL2promotion, CUtensorMapFloatOOBfill);

}

extern "C" void kernel_launch(void* const* d_in, const int* in_sizes, int n_in, void* d_out, int out_size) {
  static EncodeFn enc = nullptr;
  static void* qkv_ptr = nullptr;
  if (!enc) {
    void* fn = nullptr;
    cudaDriverEntryPointQueryResult qr;
    cudaGetDriverEntryPoint("cuTensorMapEncodeTiled", &fn, cudaEnableDefault, &qr);
    enc = (EncodeFn)fn;
    cudaGetSymbolAddress(&qkv_ptr, g_qkv);
    cudaFuncSetAttribute(fused_block, cudaFuncAttributeMaxDynamicSharedMemorySize, SMEM_BYTES);
  }
  Params P;
  P.x = (const __nv_bfloat16*)d_in[0];
  P.wqkv = (const __nv_bfloat16*)d_in[1];
  P.wg = (const __nv_bfloat16*)d_in[4];
  P.wu = (const __nv_bfloat16*)d_in[5];
  P.zero = 0;
  const cuuint32_t es[5] = {1, 1, 1, 1, 1};
  const CUtensorMapDataType BF = CU_TENSOR_MAP_DATA_TYPE_BFLOAT16;
  const CUtensorMapInterleave IL = CU_TENSOR_MAP_INTERLEAVE_NONE;
  const CUtensorMapL2promotion L2P = CU_TENSOR_MAP_L2_PROMOTION_L2_128B;
  const CUtensorMapFloatOOBfill OOB = CU_TENSOR_MAP_FLOAT_OOB_FILL_NONE;
  {
    cuuint64_t gd[2] = {640, 2048}, gs[1] = {1280};
    cuuint32_t bd[2] = {64, 128}, bo[2] = {80, 16};
    enc(&P.tmX, BF, 2, d_in[0], gd, gs, bd, es, IL, CU_TENSOR_MAP_SWIZZLE_128B, L2P, OOB);
    enc(&P.tmO, BF, 2, d_out, gd, gs, bo, es, IL, CU_TENSOR_MAP_SWIZZLE_NONE, L2P, OOB);
  }
  {
    cuuint64_t gd[3] = {8, 2048, 80}, gs[2] = {1280, 16};
    cuuint32_t bd[3] = {8, 64, 10};
    enc(&P.tmR, BF, 3, d_in[0], gd, gs, bd, es, IL, CU_TENSOR_MAP_SWIZZLE_NONE, L2P, OOB);
  }
  {
    cuuint64_t gd[3] = {64, 640, 30}, gs[2] = {3840, 128};
    cuuint32_t bd[3] = {64, 64, 2};
    enc(&P.tmW, BF, 3, d_in[1], gd, gs, bd, es, IL, CU_TENSOR_MAP_SWIZZLE_128B, L2P, OOB);
  }
  {
    cuuint64_t gd[2] = {256, 16 * 288}, gs[1] = {2048};
    cuuint32_t bd[2] = {32, 10};
    enc(&P.tmQ, CU_TENSOR_MAP_DATA_TYPE_UINT64, 2, qkv_ptr, gd, gs, bd, es, IL, CU_TENSOR_MAP_SWIZZLE_NONE, L2P, OOB);
  }
  {
    cuuint64_t gd[3] = {64, 640, 24}, gs[2] = {3072, 128};
    cuuint32_t bd[3] = {64, 32, 3};
    enc(&P.tmG, BF, 3, d_in[4], gd, gs, bd, es, IL, CU_TENSOR_MAP_SWIZZLE_128B, L2P, OOB);
    enc(&P.tmU, BF, 3, d_in[5], gd, gs, bd, es, IL, CU_TENSOR_MAP_SWIZZLE_128B, L2P, OOB);
  }
  {
    cuuint64_t gd[2] = {640, 640}, gs[1] = {1280};
    cuuint32_t bd[2] = {80, 64};
    enc(&P.tmWo, BF, 2, d_in[2], gd, gs, bd, es, IL, CU_TENSOR_MAP_SWIZZLE_NONE, L2P, OOB);
    gd[1] = 1536;
    enc(&P.tmWd, BF, 2, d_in[6], gd, gs, bd, es, IL, CU_TENSOR_MAP_SWIZZLE_NONE, L2P, OOB);
  }
  fused_block<<<132, 512, SMEM_BYTES, cudaStreamPerThread>>>(P);
}
```
